```python
import torch

def _softmax(x, axis=-1):
    return torch.softmax(x, dim=axis)
def _gelu(x):
    return torch.nn.functional.gelu(x, approximate="tanh")
def _silu(x):
    return torch.nn.functional.silu(x)
def _sigmoid(x):
    return torch.sigmoid(x)
def _layernorm(x, axis=-1, eps=1e-5):
    m = x.mean(dim=axis, keepdim=True)
    v = x.var(dim=axis, keepdim=True, unbiased=False)
    return (x - m) / torch.sqrt(v + eps)
def _scatter_add(tgt, idx, src, axis=0):
    return tgt.clone().index_add_(axis, idx, src)
def _segment_sum(src, seg, n):
    out = torch.zeros((n,) + src.shape[1:], dtype=src.dtype)
    return out.index_add_(0, seg, src)
def _pad(x, pw):
    flat = tuple(v for pair in reversed(pw) for v in pair)
    return torch.nn.functional.pad(x, flat)

kernel_name = 'parallel_sum__sliding_block_cached__swiglu_ffn__decode'

def setup_inputs():

    _w = (lambda a: (lambda t: t.to(torch.bfloat16) if t.is_floating_point() else t)(torch.as_tensor(a)))
    def _A_setup():
        B, Sq, D = 1, 1, 512
        Hq, Hkv, Sk, Dh = 32, 8, 65536, 128
        assert Hq % Hkv == 0, (Hq, Hkv)
        return {
            "x": _w((lambda *s: torch.randn(*s, dtype=torch.bfloat16) * 0.05)(B, Sq, D)),
            "k_cache": _w((lambda *s: torch.randn(*s, dtype=torch.bfloat16) * 3.2)(B, Hkv, Sk, Dh)),
            "v_cache": _w((lambda *s: torch.randn(*s, dtype=torch.bfloat16) * 1.6)(B, Hkv, Sk, Dh)),
            "wq": _w((lambda *s: torch.randn(*s, dtype=torch.bfloat16) * 3.2)(D, Hq * Dh) * (D ** -0.5)),
            "wo": _w((lambda *s: torch.randn(*s, dtype=torch.bfloat16) * 1.6)(Hq * Dh, D) * ((Hq * Dh) ** -0.5)),
        }
    _A_in = _A_setup()

    def _B_setup():
        B, S, D, F = 1, 1, 512, 1792
        return {
            "x": _w((lambda *s: torch.randn(*s, dtype=torch.bfloat16) * 0.05)(B, S, D)),
            "w_gate": _w((lambda *s: torch.randn(*s, dtype=torch.bfloat16) * 0.05)(D, F)),
            "w_up": _w((lambda *s: torch.randn(*s, dtype=torch.bfloat16) * 0.05)(D, F)),
            "w_down": _w((lambda *s: torch.randn(*s, dtype=torch.bfloat16) * 0.05)(F, D)),
        }
    _B_in = _B_setup()

    return {
        "A_x": _A_in["x"],
        "A_k_cache": _A_in["k_cache"],
        "A_v_cache": _A_in["v_cache"],
        "A_wq": _A_in["wq"],
        "A_wo": _A_in["wo"],
        "B_x": _B_in["x"],
        "B_w_gate": _B_in["w_gate"],
        "B_w_up": _B_in["w_up"],
        "B_w_down": _B_in["w_down"],
    }

def reference(A_x, A_k_cache, A_v_cache, A_wq, A_wo, B_x, B_w_gate, B_w_up, B_w_down):
    def _A_ref(x, k_cache, v_cache, wq, wo):
        B, Sq, D = x.shape
        Hq, Dh = 32, 128
        Hkv, Sk = k_cache.shape[1], k_cache.shape[2]
        W = min(4096, max(256, Sk // 4))
        rep = Hq // Hkv
        q = (lambda x, *d: x.permute(*d))((x @ wq).reshape(B, Sq, Hq, Dh), 0, 2, 1, 3)
        k = (lambda x, n, axis: torch.repeat_interleave(x, n, dim=axis))(k_cache[:, :, Sk - W:, :], rep, axis=1)
        v = (lambda x, n, axis: torch.repeat_interleave(x, n, dim=axis))(v_cache[:, :, Sk - W:, :], rep, axis=1)
        scores = torch.einsum("bhqd,bhkd->bhqk", q, k) * (Dh ** -0.5)
        p = _softmax(scores, axis=-1)
        o = torch.einsum("bhqk,bhkd->bhqd", p, v)
        return (lambda x, *d: x.permute(*d))(o, 0, 2, 1, 3).reshape(B, Sq, Hq * Dh) @ wo

    def _B_ref(x, w_gate, w_up, w_down):
        g = _silu(x @ w_gate)
        u = x @ w_up
        return (g * u) @ w_down

    x = A_x
    xn = _layernorm(x, axis=-1)
    return x + _A_ref(xn, A_k_cache, A_v_cache, A_wq, A_wo) + _B_ref(xn, B_w_gate, B_w_up, B_w_down)
```

```cpp
#include <cuda_runtime.h>
#include <cuda_bf16.h>
#include <cuda.h>
#include <stdint.h>

namespace {

constexpr int D_MODEL = 512, HKV = 8, SK = 65536, DH = 128, WIN = 4096, FF = 1792;
constexpr int NCTA = 128, NFFN = FF / 16, NTHREADS = 320;
#define DEP 0xFFDE012345678ull
constexpr int NFREE = ((DEP >> 40) & 0xFF) == 0xFF ? 3 : ((DEP >> 44) & 0xF) == 0xF ? 2 : 1;
#define PT 665
#define PS 0
#define NSIG 0
#define PH (j * 8)
#define PT2 (PT * 15 / 16)
#define PT3 (PT * 2)
#define PT4 PT
#define QD 2000
#define ODJ 80
#define OD 1400
constexpr uint32_t TAGM = 7u;
constexpr int SPIN_LIMIT = 1 << 20;

constexpr int SM_W = 0;
constexpr int SM_K = 32768;
constexpr int SM_V = SM_K + 65536;
constexpr int SM_G = SM_V + 65536;
constexpr int SM_U = SM_G + 16384;
constexpr int SM_D = SM_U + 16384;
constexpr int SM_BAR = SM_D + 16384;
constexpr int SM_PART = SM_BAR + 256;
constexpr int SM_Q = SM_PART + 1024;
constexpr int SM_P = SM_Q + 1088;
constexpr int SM_MX = SM_P + 2112;
constexpr int SM_SUM = SM_MX + 128;
constexpr int SM_O = SM_SUM + 128;
constexpr int SM_PART2 = SM_O + 128;
constexpr int SM_PROF = SM_PART2 + 4096;
constexpr int SM_TOTAL = SM_PROF + 256;

struct __align__(64) Maps { CUtensorMap m[6]; };

__device__ uint32_t g_epoch = 1;
__device__ __align__(128) uint32_t g_q[NCTA * 32];
__device__ __align__(128) uint32_t g_o[NCTA * 16 * 32];
__device__ __align__(128) uint2 g_ml[HKV * 4 * 16];
__device__ __align__(128) unsigned long long g_acc[D_MODEL];

#define STAMP(i)
#define FLUSH_STAMPS()

__device__ __forceinline__ void mbar_init(uint32_t a, int n) { asm volatile("mbarrier.init.shared::cta.b64 [%0], %1;" ::"r"(a), "r"(n) : "memory"); }
__device__ __forceinline__ void mbar_expect(uint32_t a, int bytes) {
    asm volatile("mbarrier.arrive.expect_tx.shared::cta.b64 _, [%0], %1;" ::"r"(a), "r"(bytes) : "memory");
}
__device__ __forceinline__ void mbar_wait(uint32_t a) {
    uint32_t ok;
    int it = 0;
#pragma unroll 1
    do {
        asm volatile("{\n.reg .pred p;\nmbarrier.try_wait.parity.shared::cta.b64 p, [%1], 0;\nselp.u32 %0, 1, 0, p;\n}"
                     : "=r"(ok) : "r"(a) : "memory");
    } while (!ok && ++it < 4096);
}
__device__ __forceinline__ void tma3d(uint32_t dst, const CUtensorMap* m, int c0, int c1, int c2, uint32_t bar) {
    asm volatile("cp.async.bulk.tensor.3d.shared::cluster.global.mbarrier::complete_tx::bytes [%0], [%1, {%3, %4, %5}], [%2];"
                 ::"r"(dst), "l"(m), "r"(bar), "r"(c0), "r"(c1), "r"(c2) : "memory");
}
__device__ __forceinline__ void st_pair(uint32_t dst, uint32_t bar, uint32_t a, uint32_t b) {
#pragma unroll
    for (int r = 0; r < 2; r++) {
        uint32_t d, m;
        asm("mapa.shared::cluster.u32 %0, %1, %2;" : "=r"(d) : "r"(dst), "r"(r));
        asm("mapa.shared::cluster.u32 %0, %1, %2;" : "=r"(m) : "r"(bar), "r"(r));
        asm volatile("st.async.weak.shared::cluster.mbarrier::complete_tx::bytes.v2.b32 [%0], {%1,%2}, [%3];"
                     ::"r"(d), "r"(a), "r"(b), "r"(m) : "memory");
    }
}
__device__ __forceinline__ void cluster_arrive() { asm volatile("barrier.cluster.arrive.relaxed.aligned;" ::: "memory"); }
__device__ __forceinline__ void cluster_wait() { asm volatile("barrier.cluster.wait.acquire.aligned;" ::: "memory"); }
__device__ __forceinline__ void bar_sync(int id, int n) { asm volatile("bar.sync %0, %1;" ::"r"(id), "r"(n) : "memory"); }
__device__ __forceinline__ void bar_arrive(int id, int n) { asm volatile("bar.arrive %0, %1;" ::"r"(id), "r"(n) : "memory"); }
__device__ __forceinline__ void ldsm4(uint32_t (&r)[4], uint32_t a) {
    asm volatile("ldmatrix.sync.aligned.m8n8.x4.shared.b16 {%0,%1,%2,%3}, [%4];"
                 : "=r"(r[0]), "=r"(r[1]), "=r"(r[2]), "=r"(r[3]) : "r"(a) : "memory");
}
__device__ __forceinline__ void ldsm4t(uint32_t (&r)[4], uint32_t a) {
    asm volatile("ldmatrix.sync.aligned.m8n8.x4.trans.shared.b16 {%0,%1,%2,%3}, [%4];"
                 : "=r"(r[0]), "=r"(r[1]), "=r"(r[2]), "=r"(r[3]) : "r"(a) : "memory");
}
__device__ __forceinline__ void mma(float (&c)[4], uint32_t a0, uint32_t a1, uint32_t a2, uint32_t a3, uint32_t b0, uint32_t b1) {
    asm volatile("mma.sync.aligned.m16n8k16.row.col.f32.bf16.bf16.f32 {%0,%1,%2,%3}, {%4,%5,%6,%7}, {%8,%9}, {%0,%1,%2,%3};"
                 : "+f"(c[0]), "+f"(c[1]), "+f"(c[2]), "+f"(c[3])
                 : "r"(a0), "r"(a1), "r"(a2), "r"(a3), "r"(b0), "r"(b1));
}
__device__ __forceinline__ uint4 ld_poll4(const void* p) {
    uint4 v;
    asm volatile("ld.relaxed.gpu.global.v4.u32 {%0,%1,%2,%3}, [%4];" : "=r"(v.x), "=r"(v.y), "=r"(v.z), "=r"(v.w) : "l"(p) : "memory");
    return v;
}
__device__ __forceinline__ uint2 ld_poll2(const void* p) {
    uint2 v;
    asm volatile("ld.relaxed.gpu.global.v2.u32 {%0,%1}, [%2];" : "=r"(v.x), "=r"(v.y) : "l"(p) : "memory");
    return v;
}
__device__ __forceinline__ void st_pub1(void* p, uint32_t v) { asm volatile("st.relaxed.gpu.global.u32 [%0], %1;" ::"l"(p), "r"(v) : "memory"); }
__device__ __forceinline__ void st_pub2(void* p, uint32_t a, uint32_t b) {
    asm volatile("st.relaxed.gpu.global.v2.u32 [%0], {%1,%2};" ::"l"(p), "r"(a), "r"(b) : "memory");
}
__device__ __forceinline__ bool tagged(uint4 v, uint32_t tag) { return (((v.x ^ tag) | (v.y ^ tag) | (v.z ^ tag) | (v.w ^ tag)) & TAGM) == 0; }
__device__ __forceinline__ void delay(uint32_t cycles) {
    uint32_t t0, t1;
    asm volatile("mov.u32 %0, %%clock;" : "=r"(t0));
    do { asm volatile("mov.u32 %0, %%clock;" : "=r"(t1)); } while (t1 - t0 < cycles);
}
__device__ __forceinline__ uint32_t now_ns() { uint32_t t; asm volatile("mov.u32 %0, %%globaltimer_lo;" : "=r"(t)); return t; }
__device__ __forceinline__ unsigned long long to_fix(float v) { return ((unsigned long long)__float2ll_rn(v * 268435456.f) << 8) | 1ull; }
__device__ __forceinline__ float from_fix(unsigned long long a) { return __ll2float_rn((long long)a >> 8) * (1.f / 268435456.f); }
__device__ __forceinline__ uint32_t tagf(float f, uint32_t tag) { return (__float_as_uint(f) & ~TAGM) | tag; }
__device__ __forceinline__ float untag(uint32_t u) { return __uint_as_float(u & ~TAGM); }
__device__ __forceinline__ float bfr(float f) { return __bfloat162float(__float2bfloat16_rn(f)); }
__device__ __forceinline__ float bflo(uint32_t u) { return __uint_as_float(u << 16); }
__device__ __forceinline__ float bfhi(uint32_t u) { return __uint_as_float(u & 0xffff0000u); }
__device__ __forceinline__ uint32_t pack_bf(float lo, float hi) {
    __nv_bfloat162 v = __floats2bfloat162_rn(lo, hi);
    return *reinterpret_cast<uint32_t*>(&v);
}
__device__ __forceinline__ float sel4(int t, float a, float b, float c, float d) { return (t & 2) ? ((t & 1) ? d : c) : ((t & 1) ? b : a); }

__global__ void __cluster_dims__(2, 1, 1) __launch_bounds__(NTHREADS, 1)
fused_decode_kernel(const __grid_constant__ Maps maps, const __nv_bfloat16* __restrict__ x,
                    const __nv_bfloat16* __restrict__ wq, __nv_bfloat16* __restrict__ out) {
    extern __shared__ __align__(1024) uint8_t smem[];
    const uint32_t sb = (uint32_t)__cvta_generic_to_shared(smem);
    const int tid = threadIdx.x, lane = tid & 31;
    const int warp = tid >> 5;
    const int cta = blockIdx.x, h = cta >> 4, j = cta & 15, pair = cta >> 1, rank = cta & 1;
    const uint32_t bars = sb + SM_BAR;
    const bool has_ffn = cta < NFFN;

    if (warp == 8) {
        const int u = (!has_ffn && lane >= 8) ? lane + 3 : lane;
        if (lane < 6) asm volatile("prefetch.tensormap [%0];" ::"l"(&maps.m[lane]) : "memory");
        if (lane < 13 || lane == 15 || lane == 16) mbar_init(bars + 8 * lane, 1);
        asm volatile("fence.proxy.async.shared::cta;" ::: "memory");
        __syncwarp();
        const int mi = u < 8 ? (u >> 2) : min(u - 6, 5);
        const int c0 = (u == 8 || u == 9) ? pair * 32 : 0;
        const int c1 = u < 8 ? h * SK + (SK - WIN) + j * 256 + 64 * (u & 3) : (u < 10 ? 0 : (u == 10 ? pair * 32 : pair * 64 + (u - 11) * 32));
        const int c2 = u < 8 ? 0 : (u < 10 ? rank : 4 * rank);
        const uint32_t dst = sb + (u < 11 ? SM_K + u * 16384 : SM_W + (u - 11) * 16384);
        const int n = has_ffn ? 13 : 10;
        if (lane == 0) STAMP(0);
        uint32_t due = now_ns() + PS + (PH) * PT / 128;
#pragma unroll 1
        for (int i = 0; i < n; i++) {
            if (i == NSIG) {
                if (lane == 15 || lane == 16) mbar_expect(bars + 8 * lane, lane == 15 ? 4096 : 128);
                asm volatile("fence.mbarrier_init.release.cluster;" ::: "memory");
                cluster_arrive();
                bar_arrive(1, 288);
                bar_sync(5, 96);
            }
            if (i == n - 2) {
                bar_sync(2, 288);
                asm volatile("fence.proxy.async.shared::cta;" ::: "memory");
            }
            if (i >= NFREE) mbar_wait(bars + 8 * (int)((DEP >> (48 - 4 * i)) & 15));
            for (int it = 0; it < 4096 && (int)(now_ns() - due) < 0; it++) {}
            due += i < 7 ? PT : (i < 10 ? (has_ffn ? PT2 : PT3) : PT4);
            if (lane == i) {
                STAMP(16 + i);
                mbar_expect(bars + 8 * u, 16384);
                tma3d(dst, &maps.m[mi], c0, c1, c2, bars + 8 * u);
            }
            __syncwarp();
        }
        return;
    }
    if (warp == 9) {
        const uint32_t tag = __ldcg(&g_epoch);
        cluster_arrive();
        cluster_wait();
        {
            const uint2* pml = g_ml + (h * 16 + (lane >> 3)) * 4 + (j >> 2);
            const uint4* po = reinterpret_cast<const uint4*>(g_o + cta * 512) + lane;
            uint2 ml[4];
            uint4 v[4];
            bar_sync(7, 64);
            delay(OD + (15 - j) * ODJ);
#pragma unroll
            for (int i = 0; i < 4; i++) ml[i] = ld_poll2(pml + 16 * i);
#pragma unroll
            for (int i = 0; i < 4; i++) v[i] = ld_poll4(po + 32 * i);
#pragma unroll 1
            for (int it = 0; it < SPIN_LIMIT; it++) {
                bool ok = true;
#pragma unroll
                for (int i = 0; i < 4; i++) {
                    if (!tagged(v[i], tag)) { v[i] = ld_poll4(po + 32 * i); ok = false; }
                    if (((ml[i].x ^ tag) | (ml[i].y ^ tag)) & TAGM) { ml[i] = ld_poll2(pml + 16 * i); ok = false; }
                }
                if (__all_sync(~0u, ok)) break;
            }
            if (lane == 0) STAMP(14);
            float M = fmaxf(fmaxf(untag(ml[0].x), untag(ml[1].x)), fmaxf(untag(ml[2].x), untag(ml[3].x)));
            M = fmaxf(M, __shfl_xor_sync(~0u, M, 8));
            M = fmaxf(M, __shfl_xor_sync(~0u, M, 16));
            float a0 = 0.f, a1 = 0.f, a2 = 0.f, a3 = 0.f, L = 0.f;
#pragma unroll
            for (int i = 0; i < 4; i++) {
                const float w = __expf(untag(ml[i].x) - M);
                L += w * untag(ml[i].y);
                a0 += w * untag(v[i].x); a1 += w * untag(v[i].y);
                a2 += w * untag(v[i].z); a3 += w * untag(v[i].w);
            }
#pragma unroll
            for (int s = 8; s < 32; s <<= 1) {
                L += __shfl_xor_sync(~0u, L, s);
                a0 += __shfl_xor_sync(~0u, a0, s); a1 += __shfl_xor_sync(~0u, a1, s);
                a2 += __shfl_xor_sync(~0u, a2, s); a3 += __shfl_xor_sync(~0u, a3, s);
            }
            L = __fdividef(1.f, L);
            if (lane < 8) st_pair(sb + SM_O + rank * 64 + lane * 8, bars + 128, pack_bf(a0 * L, a1 * L), pack_bf(a2 * L, a3 * L));
            if (lane == 0) STAMP(2);
        }
        return;
    }

    const int g = lane >> 2, t = lane & 3;
    const int lrow = (lane & 7) + ((lane >> 4) << 3);
    const int lch = (lane >> 3) & 1;
    {
        const char* src = reinterpret_cast<const char*>(wq) + (size_t)(warp * 32 + g) * 8192 + cta * 64 + t * 16;
        const uint32_t dst = sb + SM_W + (warp * 64 + g) * 64 + ((t ^ ((g >> 1) & 3)) << 4);
#pragma unroll
        for (int i = 0; i < 8; i++)
            asm volatile("cp.async.cg.shared.global.L2::128B [%0], [%1], 16;" ::"r"(dst + i * 512), "l"(src + (size_t)((i >> 2) * 32 + (i & 3)) * 65536) : "memory");
        if ((warp & 3) == 3) {
            const uint32_t b = bars + 8 * (13 + (warp >> 2));
            if (lane == 0) mbar_init(b, 32);
            __syncwarp();
            asm volatile("cp.async.mbarrier.arrive.noinc.shared::cta.b64 [%0];" ::"r"(b) : "memory");
            bar_arrive(5, 96);
        }
    }
    cluster_arrive();
    uint32_t xn[8];
    uint32_t* const pqo = g_q + cta * 32 + lane;
    uint2* const pml = g_ml + cta * 4 + (g & 3);
    uint32_t* const po = g_o + ((h * 16 + (t & 1) * 8 + (warp >> 1)) * 16 + j) * 32 + (warp & 1) * 16 + (t >> 1) * 8 + g;
    unsigned long long* const pa = g_acc + rank * 256 + tid;
    const int ocol = 256 * rank + 32 * warp + 8 * t + g;
    const uint32_t tag = __ldcg(&g_epoch);
    {
        const uint4 xa = __ldg(reinterpret_cast<const uint4*>(x) + lane);
        const uint4 xb = __ldg(reinterpret_cast<const uint4*>(x) + 32 + lane);
#pragma unroll
        for (int i = 0; i < 8; i++) xn[i] = __ldg(reinterpret_cast<const uint32_t*>(x) + (i >> 2) * 128 + warp * 16 + (i & 3) * 4 + t);
        if (pair == (tid >> 2)) atomicAdd(pa, to_fix(__bfloat162float(x[ocol])));
        const uint32_t xw[8] = {xa.x, xa.y, xa.z, xa.w, xb.x, xb.y, xb.z, xb.w};
        float s = 0.f;
#pragma unroll
        for (int i = 0; i < 8; i++) s += bflo(xw[i]) + bfhi(xw[i]);
#pragma unroll
        for (int o = 1; o < 32; o <<= 1) s += __shfl_xor_sync(~0u, s, o);
        const float mean = s * (1.f / D_MODEL);
        float q = 0.f;
#pragma unroll
        for (int i = 0; i < 8; i++) {
            const float a = bflo(xw[i]) - mean, b = bfhi(xw[i]) - mean;
            q += a * a + b * b;
        }
#pragma unroll
        for (int o = 1; o < 32; o <<= 1) q += __shfl_xor_sync(~0u, q, o);
        const float mb = bfr(mean);
        float sd;
        asm("sqrt.approx.f32 %0, %1;" : "=f"(sd) : "f"(bfr(bfr(q * (1.f / D_MODEL)) + 1e-5f)));
        const float rden = __fdividef(1.f, bfr(sd));
#pragma unroll
        for (int i = 0; i < 8; i++) xn[i] = pack_bf(bfr(bflo(xn[i]) - mb) * rden, bfr(bfhi(xn[i]) - mb) * rden);
    }
    asm volatile("cp.async.wait_all;" ::: "memory");
    __syncwarp();
    if (tid == 0) STAMP(4);
    {
        float c0[4] = {0.f, 0.f, 0.f, 0.f}, c1[4] = {0.f, 0.f, 0.f, 0.f};
        const uint32_t base = sb + SM_W + (warp * 64 + lrow) * 64;
        const int sw = (lane >> 1) & 3;
#pragma unroll
        for (int s = 0; s < 4; s++) {
            uint32_t a[4], b[4];
            ldsm4t(a, base + s * 1024 + ((lch ^ sw) << 4));
            ldsm4t(b, base + s * 1024 + (((2 + lch) ^ sw) << 4));
            mma(c0, a[0], a[1], a[2], a[3], xn[2 * s], xn[2 * s + 1]);
            mma(c1, b[0], b[1], b[2], b[3], xn[2 * s], xn[2 * s + 1]);
        }
        reinterpret_cast<float*>(smem + SM_PART)[warp * 32 + 8 * t + g] = sel4(t, c0[0], c0[2], c1[0], c1[2]);
    }
    bar_arrive(2, 288);
    bar_sync(1, 288);
    if (warp == 0) {
        float s = 0.f;
#pragma unroll
        for (int w = 0; w < 8; w++) s += reinterpret_cast<const float*>(smem + SM_PART)[w * 32 + lane];
        st_pub1(pqo, __float_as_uint(bfr(s)) | tag);
    }
    if (tid == 0) STAMP(12);
    if (tid < 128) {
        const uint4* pq = reinterpret_cast<const uint4*>(g_q + h * 512) + tid;
        uint4 v;
        delay(QD);
#pragma unroll 1
        for (int it = 0; it < SPIN_LIMIT; it++) {
            v = ld_poll4(pq);
            if (tagged(v, tag)) break;
        }
        *reinterpret_cast<uint2*>(smem + SM_Q + warp * 272 + lane * 8) =
            make_uint2(__byte_perm(v.x, v.y, 0x7632), __byte_perm(v.z, v.w, 0x7632));
    }
    bar_sync(3, 256);
    if (tid == 0) STAMP(5);
    const int head = g & 3;
    float sc[4];
    {
        uint32_t qa[4][4];
#pragma unroll
        for (int i = 0; i < 4; i++) ldsm4(qa[i], sb + SM_Q + (lane & 3) * 272 + (4 * i + (lane >> 3)) * 16);
        mbar_wait(bars + 8 * (warp >> 1));
        if (tid == 224) STAMP(13);
        float c[4][4];
        const uint32_t kb = sb + SM_K + (warp >> 1) * 16384 + (32 * (warp & 1) + (lane & 7)) * 128;
#pragma unroll
        for (int n = 0; n < 4; n++) {
#pragma unroll
            for (int e = 0; e < 4; e++) c[n][e] = 0.f;
#pragma unroll
            for (int i = 0; i < 4; i++) {
                uint32_t b[4];
                ldsm4(b, kb + n * 1024 + (i >> 1) * 8192 + (((4 * (i & 1) + (lane >> 3)) ^ (lane & 7)) << 4));
                mma(c[n], qa[i][0], 0u, qa[i][1], 0u, b[0], b[1]);
                mma(c[n], qa[i][2], 0u, qa[i][3], 0u, b[2], b[3]);
            }
        }
        const bool up = g >= 4;
        const float scale = 0.08838834764831845f;
        sc[0] = bfr(bfr(up ? c[2][0] : c[0][0]) * scale);
        sc[1] = bfr(bfr(up ? c[2][1] : c[0][1]) * scale);
        sc[2] = bfr(bfr(up ? c[3][0] : c[1][0]) * scale);
        sc[3] = bfr(bfr(up ? c[3][1] : c[1][1]) * scale);
    }
    float mcta;
    {
        float m = fmaxf(fmaxf(sc[0], sc[1]), fmaxf(sc[2], sc[3]));
        m = fmaxf(m, __shfl_xor_sync(~0u, m, 1));
        m = fmaxf(m, __shfl_xor_sync(~0u, m, 2));
        m = fmaxf(m, __shfl_xor_sync(~0u, m, 16));
        if (t == 0 && g < 4) reinterpret_cast<float*>(smem + SM_MX)[g * 8 + warp] = m;
        bar_sync(3, 256);
        const float4 m0 = *reinterpret_cast<const float4*>(smem + SM_MX + head * 32);
        const float4 m1 = *reinterpret_cast<const float4*>(smem + SM_MX + head * 32 + 16);
        mcta = fmaxf(fmaxf(fmaxf(m0.x, m0.y), fmaxf(m0.z, m0.w)), fmaxf(fmaxf(m1.x, m1.y), fmaxf(m1.z, m1.w)));
        const float p0 = __expf(sc[0] - mcta), p1 = __expf(sc[1] - mcta), p2 = __expf(sc[2] - mcta), p3 = __expf(sc[3] - mcta);
        uint8_t* pp = smem + SM_P + head * 528 + (32 * warp + 16 * (g >> 2) + 2 * t) * 2;
        *reinterpret_cast<uint32_t*>(pp) = pack_bf(p0, p1);
        *reinterpret_cast<uint32_t*>(pp + 16) = pack_bf(p2, p3);
        float l = (p0 + p1) + (p2 + p3);
        l += __shfl_xor_sync(~0u, l, 1);
        l += __shfl_xor_sync(~0u, l, 2);
        l += __shfl_xor_sync(~0u, l, 16);
        if (t == 0 && g < 4) reinterpret_cast<float*>(smem + SM_SUM)[g * 8 + warp] = l;
        bar_sync(3, 256);
        if (warp == 0 && t == 0 && g < 4) {
            const float4 l0 = *reinterpret_cast<const float4*>(smem + SM_SUM + head * 32);
            const float4 l1 = *reinterpret_cast<const float4*>(smem + SM_SUM + head * 32 + 16);
            const float ls = ((l0.x + l0.y) + (l0.z + l0.w)) + ((l1.x + l1.y) + (l1.z + l1.w));
            st_pub2(pml, tagf(mcta, tag), tagf(ls, tag));
        }
    }
    if (tid == 0) STAMP(6);
    {
        float c0[4] = {0.f, 0.f, 0.f, 0.f}, c1[4] = {0.f, 0.f, 0.f, 0.f};
        const uint32_t pb = sb + SM_P + (lane & 3) * 528 + (lane >> 3) * 16;
        const uint32_t vb = sb + SM_V + (warp >> 2) * 8192 + lrow * 128 + (((2 * (warp & 3) + lch) ^ (lane & 7)) << 4);
#pragma unroll
        for (int i = 0; i < 4; i++) {
            uint32_t p0[4], p1[4], a[4][4];
            ldsm4(p0, pb + i * 128);
            ldsm4(p1, pb + i * 128 + 64);
            mbar_wait(bars + 32 + 8 * i);
#pragma unroll
            for (int s = 0; s < 4; s++) ldsm4t(a[s], vb + i * 16384 + s * 2048);
            mma(c0, a[0][0], a[0][1], a[0][2], a[0][3], p0[0], p0[1]);
            mma(c1, a[1][0], a[1][1], a[1][2], a[1][3], p0[2], p0[3]);
            mma(c0, a[2][0], a[2][1], a[2][2], a[2][3], p1[0], p1[1]);
            mma(c1, a[3][0], a[3][1], a[3][2], a[3][3], p1[2], p1[3]);
        }
        const bool up = t >= 2;
        const float v0 = up ? c0[2] + c1[2] : c0[0] + c1[0];
        const float v1 = up ? c0[3] + c1[3] : c0[1] + c1[1];
        st_pub1(po, tagf(v0, tag));
        st_pub1(po + 4 * 512, tagf(v1, tag));
        if (warp == 0) bar_arrive(7, 64);
    }
    if (tid == 0) STAMP(7);
    float y0[4] = {0.f, 0.f, 0.f, 0.f}, y1[4] = {0.f, 0.f, 0.f, 0.f};
    const uint32_t wofs = (warp >> 1) * 4096 + lrow * 128 + (((4 * (warp & 1) + lch) ^ (lane & 7)) << 4);
    if (has_ffn) {
        float c[4][4];
        const uint32_t base = sb + SM_G + (warp * 32 + lrow) * 64 + ((lch ^ ((lane >> 1) & 3)) << 4);
        const uint32_t x0 = rank ? xn[4] : xn[0], x1 = rank ? xn[5] : xn[1], x2 = rank ? xn[6] : xn[2], x3 = rank ? xn[7] : xn[3];
        cluster_wait();
#pragma unroll
        for (int m = 0; m < 4; m++) {
            uint32_t a[4], b[4];
            if (!(m & 1)) mbar_wait(bars + 64 + 4 * m);
            ldsm4t(a, (base ^ ((m & 1) << 5)) + (m >> 1) * 16384);
            ldsm4t(b, (base ^ ((m & 1) << 5)) + (m >> 1) * 16384 + 1024);
#pragma unroll
            for (int e = 0; e < 4; e++) c[m][e] = 0.f;
            mma(c[m], a[0], a[1], a[2], a[3], x0, x1);
            mma(c[m], b[0], b[1], b[2], b[3], x2, x3);
        }
        st_pair(sb + SM_PART2 + (rank * 8 + warp) * 256 + (8 * t + g) * 8, bars + 120,
                __float_as_uint(sel4(t, c[0][0], c[0][2], c[1][0], c[1][2])), __float_as_uint(sel4(t, c[2][0], c[2][2], c[3][0], c[3][2])));
        mbar_wait(bars + 120);
        float gs = 0.f, us = 0.f;
#pragma unroll
        for (int w = 0; w < 16; w++) {
            const float2 v = reinterpret_cast<const float2*>(smem + SM_PART2)[w * 32 + lane];
            gs += v.x;
            us += v.y;
        }
        gs = bfr(gs);
        const float hv = bfr(__fdividef(gs, 1.f + __expf(-gs))) * bfr(us);
        const uint32_t hp = pack_bf(hv, __shfl_down_sync(~0u, hv, 1));
        uint32_t hb[4];
#pragma unroll
        for (int i = 0; i < 4; i++) hb[i] = __shfl_sync(~0u, hp, 8 * i + 2 * t);
        mbar_wait(bars + 80);
#pragma unroll
        for (int s = 0; s < 2; s++) {
            uint32_t a[4], b[4];
            ldsm4t(a, sb + SM_D + s * 2048 + wofs);
            ldsm4t(b, sb + SM_D + s * 2048 + (wofs ^ 32));
            mma(y0, a[0], a[1], a[2], a[3], hb[2 * s], hb[2 * s + 1]);
            mma(y1, b[0], b[1], b[2], b[3], hb[2 * s], hb[2 * s + 1]);
        }
    }
    if (tid == 0) STAMP(8);
    mbar_wait(bars + 128);
    {
        uint32_t ob[8];
#pragma unroll
        for (int i = 0; i < 8; i++) ob[i] = *reinterpret_cast<const uint32_t*>(smem + SM_O + i * 16 + t * 4);
#pragma unroll
        for (int s = 0; s < 4; s++) {
            uint32_t a[4], b[4];
            if (!(s & 1)) mbar_wait(bars + 88 + 4 * s);
            if (s == 2 && lane == 0 && warp == 7) STAMP(9);
            ldsm4t(a, sb + SM_W + (s >> 1) * 16384 + (s & 1) * 2048 + wofs);
            ldsm4t(b, sb + SM_W + (s >> 1) * 16384 + (s & 1) * 2048 + (wofs ^ 32));
            mma(y0, a[0], a[1], a[2], a[3], ob[2 * s], ob[2 * s + 1]);
            mma(y1, b[0], b[1], b[2], b[3], ob[2 * s], ob[2 * s + 1]);
        }
        const unsigned long long f = to_fix(sel4(t, y0[0], y0[2], y1[0], y1[2]));
        if (lane == 0 && warp == 7) STAMP(10);
        const unsigned long long a = atomicAdd(pa, f) + f;
        if ((a & 255) == NCTA / 2 + 1) {
            out[ocol] = __float2bfloat16_rn(from_fix(a));
            *pa = 0;
            if (ocol == 0) g_epoch = tag == TAGM ? 1u : tag + 1;
        }
    }
}

typedef CUresult (*EncodeFn)(CUtensorMap*, CUtensorMapDataType, cuuint32_t, void*, const cuuint64_t*, const cuuint64_t*,
                             const cuuint32_t*, const cuuint32_t*, CUtensorMapInterleave, CUtensorMapSwizzle,
                             CUtensorMapL2promotion, CUtensorMapFloatOOBfill);

void make_map(EncodeFn enc, CUtensorMap* m, void* p, uint64_t d0, uint64_t d1, uint64_t d2, uint64_t s1, uint64_t s2,
              uint32_t b0, uint32_t b1, uint32_t b2, CUtensorMapSwizzle sw) {
    cuuint64_t gd[3] = {d0, d1, d2};
    cuuint64_t gs[2] = {s1, s2};
    cuuint32_t bd[3] = {b0, b1, b2};
    cuuint32_t es[3] = {1, 1, 1};
    enc(m, CU_TENSOR_MAP_DATA_TYPE_BFLOAT16, 3, p, gd, gs, bd, es, CU_TENSOR_MAP_INTERLEAVE_NONE, sw,
        CU_TENSOR_MAP_L2_PROMOTION_L2_256B, CU_TENSOR_MAP_FLOAT_OOB_FILL_NONE);
}

}

extern "C" void kernel_launch(void* const* d_in, const int* in_sizes, int n_in, void* d_out, int out_size) {
    static EncodeFn enc = nullptr;
    if (!enc) {
        void* fn = nullptr;
        cudaDriverEntryPointQueryResult qr;
        cudaGetDriverEntryPoint("cuTensorMapEncodeTiled", &fn, cudaEnableDefault, &qr);
        enc = (EncodeFn)fn;
        cudaFuncSetAttribute(fused_decode_kernel, cudaFuncAttributeMaxDynamicSharedMemorySize, SM_TOTAL);
    }
    Maps m;
    make_map(enc, &m.m[0], d_in[1], 64, (uint64_t)HKV * SK, 2, DH * 2, 128, 64, 64, 2, CU_TENSOR_MAP_SWIZZLE_128B);
    make_map(enc, &m.m[1], d_in[2], 64, (uint64_t)HKV * SK, 2, DH * 2, 128, 64, 64, 2, CU_TENSOR_MAP_SWIZZLE_128B);
    make_map(enc, &m.m[2], d_in[6], FF, 256, 2, FF * 2, FF * 2 * 256, 32, 256, 1, CU_TENSOR_MAP_SWIZZLE_64B);
    make_map(enc, &m.m[3], d_in[7], FF, 256, 2, FF * 2, FF * 2 * 256, 32, 256, 1, CU_TENSOR_MAP_SWIZZLE_64B);
    make_map(enc, &m.m[4], d_in[8], 64, FF, 8, D_MODEL * 2, 128, 64, 32, 4, CU_TENSOR_MAP_SWIZZLE_128B);
    make_map(enc, &m.m[5], d_in[4], 64, 4096, 8, D_MODEL * 2, 128, 64, 32, 4, CU_TENSOR_MAP_SWIZZLE_128B);
    fused_decode_kernel<<<NCTA, NTHREADS, SM_TOTAL>>>(m, (const __nv_bfloat16*)d_in[0], (const __nv_bfloat16*)d_in[3],
                                                      (__nv_bfloat16*)d_out);
}
```

```cpp
#include <cuda_runtime.h>
#include <cuda_bf16.h>
#include <cuda.h>
#include <stdint.h>

namespace {

constexpr int D_MODEL = 512, HKV = 8, SK = 65536, DH = 128, WIN = 4096, FF = 1792;
constexpr int NCTA = 128, NFFN = FF / 16, NTHREADS = 320;
#define DEP 0xFFDE012345678ull
constexpr int NFREE = ((DEP >> 40) & 0xFF) == 0xFF ? 3 : ((DEP >> 44) & 0xF) == 0xF ? 2 : 1;
#define PT 665
#define PS 750
#define PH (j * 8)
#define PT2 (PT * 15 / 16)
#define PT3 (PT * 2)
#define PT4 PT
#define ACG 8
#define ACS 32
#define NDUM 0
#define QD 2000
#define ODJ 80
#define OD 1400
constexpr uint32_t TAGM = 7u;
constexpr int SPIN_LIMIT = 1 << 20;

constexpr int SM_W = 0;
constexpr int SM_K = 32768;
constexpr int SM_V = SM_K + 65536;
constexpr int SM_G = SM_V + 65536;
constexpr int SM_U = SM_G + 16384;
constexpr int SM_D = SM_U + 16384;
constexpr int SM_BAR = SM_D + 16384;
constexpr int SM_PART = SM_BAR + 256;
constexpr int SM_Q = SM_PART + 1024;
constexpr int SM_P = SM_Q + 1088;
constexpr int SM_MX = SM_P + 2112;
constexpr int SM_SUM = SM_MX + 128;
constexpr int SM_O = SM_SUM + 128;
constexpr int SM_PART2 = SM_O + 128;
constexpr int SM_PROF = SM_PART2 + 4096;
constexpr int SM_TOTAL = SM_PROF + 256;

struct __align__(64) Maps { CUtensorMap m[6]; };

__device__ uint32_t g_epoch = 1;
__device__ __align__(128) uint32_t g_q[NCTA * 32];
__device__ __align__(128) uint32_t g_o[NCTA * 16 * 32];
__device__ __align__(128) uint2 g_ml[HKV * 4 * 16];
__device__ __align__(128) unsigned long long g_acc[D_MODEL / ACG * ACS];

#define STAMP(i)
#define FLUSH_STAMPS()

__device__ __forceinline__ void mbar_init(uint32_t a, int n) { asm volatile("mbarrier.init.shared::cta.b64 [%0], %1;" ::"r"(a), "r"(n) : "memory"); }
__device__ __forceinline__ void mbar_expect(uint32_t a, int bytes) {
    asm volatile("mbarrier.arrive.expect_tx.shared::cta.b64 _, [%0], %1;" ::"r"(a), "r"(bytes) : "memory");
}
__device__ __forceinline__ void mbar_wait(uint32_t a) {
    uint32_t ok;
    int it = 0;
#pragma unroll 1
    do {
        asm volatile("{\n.reg .pred p;\nmbarrier.try_wait.parity.shared::cta.b64 p, [%1], 0;\nselp.u32 %0, 1, 0, p;\n}"
                     : "=r"(ok) : "r"(a) : "memory");
    } while (!ok && ++it < 4096);
}
__device__ __forceinline__ void tma3d(uint32_t dst, const CUtensorMap* m, int c0, int c1, int c2, uint32_t bar) {
    asm volatile("cp.async.bulk.tensor.3d.shared::cluster.global.mbarrier::complete_tx::bytes [%0], [%1, {%3, %4, %5}], [%2];"
                 ::"r"(dst), "l"(m), "r"(bar), "r"(c0), "r"(c1), "r"(c2) : "memory");
}
__device__ __forceinline__ void st_pair(uint32_t dst, uint32_t bar, uint32_t a, uint32_t b) {
#pragma unroll
    for (int r = 0; r < 2; r++) {
        uint32_t d, m;
        asm("mapa.shared::cluster.u32 %0, %1, %2;" : "=r"(d) : "r"(dst), "r"(r));
        asm("mapa.shared::cluster.u32 %0, %1, %2;" : "=r"(m) : "r"(bar), "r"(r));
        asm volatile("st.async.weak.shared::cluster.mbarrier::complete_tx::bytes.v2.b32 [%0], {%1,%2}, [%3];"
                     ::"r"(d), "r"(a), "r"(b), "r"(m) : "memory");
    }
}
__device__ __forceinline__ void cluster_arrive() { asm volatile("barrier.cluster.arrive.relaxed.aligned;" ::: "memory"); }
__device__ __forceinline__ void cluster_wait() { asm volatile("barrier.cluster.wait.acquire.aligned;" ::: "memory"); }
__device__ __forceinline__ void bar_sync(int id, int n) { asm volatile("bar.sync %0, %1;" ::"r"(id), "r"(n) : "memory"); }
__device__ __forceinline__ void bar_arrive(int id, int n) { asm volatile("bar.arrive %0, %1;" ::"r"(id), "r"(n) : "memory"); }
__device__ __forceinline__ void ldsm4(uint32_t (&r)[4], uint32_t a) {
    asm volatile("ldmatrix.sync.aligned.m8n8.x4.shared.b16 {%0,%1,%2,%3}, [%4];"
                 : "=r"(r[0]), "=r"(r[1]), "=r"(r[2]), "=r"(r[3]) : "r"(a) : "memory");
}
__device__ __forceinline__ void ldsm4t(uint32_t (&r)[4], uint32_t a) {
    asm volatile("ldmatrix.sync.aligned.m8n8.x4.trans.shared.b16 {%0,%1,%2,%3}, [%4];"
                 : "=r"(r[0]), "=r"(r[1]), "=r"(r[2]), "=r"(r[3]) : "r"(a) : "memory");
}
__device__ __forceinline__ void mma(float (&c)[4], uint32_t a0, uint32_t a1, uint32_t a2, uint32_t a3, uint32_t b0, uint32_t b1) {
    asm volatile("mma.sync.aligned.m16n8k16.row.col.f32.bf16.bf16.f32 {%0,%1,%2,%3}, {%4,%5,%6,%7}, {%8,%9}, {%0,%1,%2,%3};"
                 : "+f"(c[0]), "+f"(c[1]), "+f"(c[2]), "+f"(c[3])
                 : "r"(a0), "r"(a1), "r"(a2), "r"(a3), "r"(b0), "r"(b1));
}
__device__ __forceinline__ uint4 ld_poll4(const void* p) {
    uint4 v;
    asm volatile("ld.relaxed.gpu.global.v4.u32 {%0,%1,%2,%3}, [%4];" : "=r"(v.x), "=r"(v.y), "=r"(v.z), "=r"(v.w) : "l"(p) : "memory");
    return v;
}
__device__ __forceinline__ uint2 ld_poll2(const void* p) {
    uint2 v;
    asm volatile("ld.relaxed.gpu.global.v2.u32 {%0,%1}, [%2];" : "=r"(v.x), "=r"(v.y) : "l"(p) : "memory");
    return v;
}
__device__ __forceinline__ void st_pub1(void* p, uint32_t v) { asm volatile("st.relaxed.gpu.global.u32 [%0], %1;" ::"l"(p), "r"(v) : "memory"); }
__device__ __forceinline__ void st_pub2(void* p, uint32_t a, uint32_t b) {
    asm volatile("st.relaxed.gpu.global.v2.u32 [%0], {%1,%2};" ::"l"(p), "r"(a), "r"(b) : "memory");
}
__device__ __forceinline__ bool tagged(uint4 v, uint32_t tag) { return (((v.x ^ tag) | (v.y ^ tag) | (v.z ^ tag) | (v.w ^ tag)) & TAGM) == 0; }
__device__ __forceinline__ void delay(uint32_t cycles) {
    uint32_t t0, t1;
    asm volatile("mov.u32 %0, %%clock;" : "=r"(t0));
    do { asm volatile("mov.u32 %0, %%clock;" : "=r"(t1)); } while (t1 - t0 < cycles);
}
__device__ __forceinline__ uint32_t now_ns() { uint32_t t; asm volatile("mov.u32 %0, %%globaltimer_lo;" : "=r"(t)); return t; }
__device__ __forceinline__ unsigned long long to_fix(float v) { return ((unsigned long long)__float2ll_rn(v * 68719476736.f) & ~255ull) | 1ull; }
__device__ __forceinline__ float from_fix(unsigned long long a) { return __ll2float_rn((long long)a) * (1.f / 68719476736.f); }
__device__ __forceinline__ uint32_t tagf(float f, uint32_t tag) { return (__float_as_uint(f) & ~TAGM) | tag; }
__device__ __forceinline__ float untag(uint32_t u) { return __uint_as_float(u & ~TAGM); }
__device__ __forceinline__ float bfr(float f) { return __bfloat162float(__float2bfloat16_rn(f)); }
__device__ __forceinline__ float bflo(uint32_t u) { return __uint_as_float(u << 16); }
__device__ __forceinline__ float bfhi(uint32_t u) { return __uint_as_float(u & 0xffff0000u); }
__device__ __forceinline__ uint32_t pack_bf(float lo, float hi) {
    __nv_bfloat162 v = __floats2bfloat162_rn(lo, hi);
    return *reinterpret_cast<uint32_t*>(&v);
}
__device__ __forceinline__ float sel4(int t, float a, float b, float c, float d) { return (t & 2) ? ((t & 1) ? d : c) : ((t & 1) ? b : a); }

__global__ void __cluster_dims__(2, 1, 1) __launch_bounds__(NTHREADS, 1)
fused_decode_kernel(const __nv_bfloat16* __restrict__ x, const __nv_bfloat16* __restrict__ wq,
                    __nv_bfloat16* __restrict__ out, const __grid_constant__ Maps maps) {
    extern __shared__ __align__(1024) uint8_t smem[];
    const uint32_t sb = (uint32_t)__cvta_generic_to_shared(smem);
    const int tid = threadIdx.x, lane = tid & 31;
    const int warp = tid >> 5;
    const int cta = blockIdx.x, h = cta >> 4, j = cta & 15, pair = cta >> 1, rank = cta & 1;
    const uint32_t bars = sb + SM_BAR;
    const bool has_ffn = cta < NFFN;

    if (warp == 8) {
        uint32_t due = now_ns() + PS + (PH) * PT / 128;
        const int u = (!has_ffn && lane >= 8) ? lane + 3 : lane;
        if (lane == 0) {
#pragma unroll
            for (int i = 0; i < 17; i++)
                if (i < 13 || i > 14) mbar_init(bars + 8 * i, 1);
            mbar_expect(bars + 120, 4096);
            mbar_expect(bars + 128, 128);
        }
        asm volatile("fence.proxy.async.shared::cta;" ::: "memory");
        __syncwarp();
        const int mi = u < 8 ? (u >> 2) : min(u - 6, 5);
        const int c0 = (u == 8 || u == 9) ? pair * 32 : 0;
        const int c1 = u < 8 ? h * SK + (SK - WIN) + j * 256 + 64 * (u & 3) : (u < 10 ? 0 : (u == 10 ? pair * 32 : pair * 64 + (u - 11) * 32));
        const int c2 = u < 8 ? 0 : (u < 10 ? rank : 4 * rank);
        const uint32_t dst = sb + (u < 11 ? SM_K + u * 16384 : SM_W + (u - 11) * 16384);
        const int n = has_ffn ? 13 : 10;
        asm volatile("fence.mbarrier_init.release.cluster;" ::: "memory");
        cluster_arrive();
        bar_arrive(1, 288);
        if (lane == 0) STAMP(0);
#pragma unroll 1
        for (int i = 0; i < n; i++) {
            if (i == NFREE) bar_sync(5, 96);
            if (i == n - 2) {
                bar_sync(2, 288);
                asm volatile("fence.proxy.async.shared::cta;" ::: "memory");
            }
            if (i >= NFREE) mbar_wait(bars + 8 * (int)((DEP >> (48 - 4 * i)) & 15));
            for (int it = 0; it < 4096 && (int)(now_ns() - due) < 0; it++) {}
            due += i < 7 ? PT : (i < 10 ? (has_ffn ? PT2 : PT3) : PT4);
            if (lane == i) {
                STAMP(16 + i);
                mbar_expect(bars + 8 * u, 16384);
                tma3d(dst, &maps.m[mi], c0, c1, c2, bars + 8 * u);
            }
            __syncwarp();
        }
        return;
    }
    if (warp == 9) {
        const uint32_t tag = __ldcg(&g_epoch);
        cluster_arrive();
        cluster_wait();
        {
            const uint2* pml = g_ml + (h * 16 + (lane >> 3)) * 4 + (j >> 2);
            const uint4* po = reinterpret_cast<const uint4*>(g_o + cta * 512) + lane;
            uint2 ml[4];
            uint4 v[4];
            bar_sync(7, 64);
            delay(OD + (15 - j) * ODJ);
#pragma unroll
            for (int i = 0; i < 4; i++) ml[i] = ld_poll2(pml + 16 * i);
#pragma unroll
            for (int i = 0; i < 4; i++) v[i] = ld_poll4(po + 32 * i);
#pragma unroll 1
            for (int it = 0; it < SPIN_LIMIT; it++) {
                bool ok = true;
#pragma unroll
                for (int i = 0; i < 4; i++) {
                    if (!tagged(v[i], tag)) { v[i] = ld_poll4(po + 32 * i); ok = false; }
                    if (((ml[i].x ^ tag) | (ml[i].y ^ tag)) & TAGM) { ml[i] = ld_poll2(pml + 16 * i); ok = false; }
                }
                if (__all_sync(~0u, ok)) break;
            }
            if (lane == 0) STAMP(14);
            float M = fmaxf(fmaxf(untag(ml[0].x), untag(ml[1].x)), fmaxf(untag(ml[2].x), untag(ml[3].x)));
            M = fmaxf(M, __shfl_xor_sync(~0u, M, 8));
            M = fmaxf(M, __shfl_xor_sync(~0u, M, 16));
            float a0 = 0.f, a1 = 0.f, a2 = 0.f, a3 = 0.f, L = 0.f;
#pragma unroll
            for (int i = 0; i < 4; i++) {
                const float w = __expf(untag(ml[i].x) - M);
                L += w * untag(ml[i].y);
                a0 += w * untag(v[i].x); a1 += w * untag(v[i].y);
                a2 += w * untag(v[i].z); a3 += w * untag(v[i].w);
            }
#pragma unroll
            for (int s = 8; s < 32; s <<= 1) {
                L += __shfl_xor_sync(~0u, L, s);
                a0 += __shfl_xor_sync(~0u, a0, s); a1 += __shfl_xor_sync(~0u, a1, s);
                a2 += __shfl_xor_sync(~0u, a2, s); a3 += __shfl_xor_sync(~0u, a3, s);
            }
            L = __fdividef(1.f, L);
            if (lane < 8) st_pair(sb + SM_O + rank * 64 + lane * 8, bars + 128, pack_bf(a0 * L, a1 * L), pack_bf(a2 * L, a3 * L));
            if (lane == 0) STAMP(2);
        }
        return;
    }

    const int g = lane >> 2, t = lane & 3;
    const int lrow = (lane & 7) + ((lane >> 4) << 3);
    const int lch = (lane >> 3) & 1;
    {
        uint32_t ofs = (warp * 32 + g) * 8192 + cta * 64 + t * 16;
        uint32_t dst = sb + SM_W + (warp * 64 + g) * 64 + ((t ^ ((g >> 1) & 3)) << 4);
        asm volatile("" : "+r"(ofs), "+r"(dst));
        if ((ofs ^ dst) == 1u) return;
        const char* src = reinterpret_cast<const char*>(wq) + ofs;
#pragma unroll
        for (int i = 0; i < 8; i++)
            asm volatile("cp.async.cg.shared.global.L2::128B [%0], [%1], 16;" ::"r"(dst + i * 512), "l"(src + (size_t)((i >> 2) * 32 + (i & 3)) * 65536) : "memory");
        if ((warp & 3) == 3) {
            const uint32_t b = bars + 8 * (13 + (warp >> 2));
            if (lane == 0) mbar_init(b, 32);
            __syncwarp();
            asm volatile("cp.async.mbarrier.arrive.noinc.shared::cta.b64 [%0];" ::"r"(b) : "memory");
            bar_arrive(5, 96);
        }
    }
    cluster_arrive();
    uint32_t xn[8];
    uint32_t* const pqo = g_q + cta * 32 + lane;
    uint2* const pml = g_ml + cta * 4 + (g & 3);
    uint32_t* const po = g_o + ((h * 16 + (t & 1) * 8 + (warp >> 1)) * 16 + j) * 32 + (warp & 1) * 16 + (t >> 1) * 8 + g;
    unsigned long long* const pa = g_acc + (rank * 256 + tid) / ACG * ACS + tid % ACG;
    const int ocol = 256 * rank + 32 * warp + 8 * t + g;
    const uint32_t tag = __ldcg(&g_epoch);
    {
        const uint4 xa = __ldg(reinterpret_cast<const uint4*>(x) + lane);
        const uint4 xb = __ldg(reinterpret_cast<const uint4*>(x) + 32 + lane);
#pragma unroll
        for (int i = 0; i < 8; i++) xn[i] = __ldg(reinterpret_cast<const uint32_t*>(x) + (i >> 2) * 128 + warp * 16 + (i & 3) * 4 + t);
        if (pair == (tid >> 2)) atomicAdd(pa, to_fix(__bfloat162float(x[ocol])));
        const uint32_t xw[8] = {xa.x, xa.y, xa.z, xa.w, xb.x, xb.y, xb.z, xb.w};
        float s = 0.f;
#pragma unroll
        for (int i = 0; i < 8; i++) s += bflo(xw[i]) + bfhi(xw[i]);
#pragma unroll
        for (int o = 1; o < 32; o <<= 1) s += __shfl_xor_sync(~0u, s, o);
        const float mean = s * (1.f / D_MODEL);
        float q = 0.f;
#pragma unroll
        for (int i = 0; i < 8; i++) {
            const float a = bflo(xw[i]) - mean, b = bfhi(xw[i]) - mean;
            q += a * a + b * b;
        }
#pragma unroll
        for (int o = 1; o < 32; o <<= 1) q += __shfl_xor_sync(~0u, q, o);
        const float mb = bfr(mean);
        float sd;
        asm("sqrt.approx.f32 %0, %1;" : "=f"(sd) : "f"(bfr(bfr(q * (1.f / D_MODEL)) + 1e-5f)));
        const float rden = __fdividef(1.f, bfr(sd));
#pragma unroll
        for (int i = 0; i < 8; i++) xn[i] = pack_bf(bfr(bflo(xn[i]) - mb) * rden, bfr(bfhi(xn[i]) - mb) * rden);
    }
    asm volatile("cp.async.wait_all;" ::: "memory");
    __syncwarp();
    if (tid == 0) STAMP(4);
    {
        float c0[4] = {0.f, 0.f, 0.f, 0.f}, c1[4] = {0.f, 0.f, 0.f, 0.f};
        const uint32_t base = sb + SM_W + (warp * 64 + lrow) * 64;
        const int sw = (lane >> 1) & 3;
#pragma unroll
        for (int s = 0; s < 4; s++) {
            uint32_t a[4], b[4];
            ldsm4t(a, base + s * 1024 + ((lch ^ sw) << 4));
            ldsm4t(b, base + s * 1024 + (((2 + lch) ^ sw) << 4));
            mma(c0, a[0], a[1], a[2], a[3], xn[2 * s], xn[2 * s + 1]);
            mma(c1, b[0], b[1], b[2], b[3], xn[2 * s], xn[2 * s + 1]);
        }
        reinterpret_cast<float*>(smem + SM_PART)[warp * 32 + 8 * t + g] = sel4(t, c0[0], c0[2], c1[0], c1[2]);
    }
    bar_arrive(2, 288);
    bar_sync(1, 288);
    if (warp == 0) {
        float s = 0.f;
#pragma unroll
        for (int w = 0; w < 8; w++) s += reinterpret_cast<const float*>(smem + SM_PART)[w * 32 + lane];
        st_pub1(pqo, __float_as_uint(bfr(s)) | tag);
    }
    if (tid == 0) STAMP(12);
    if (tid < 128) {
        const uint4* pq = reinterpret_cast<const uint4*>(g_q + h * 512) + tid;
        uint4 v;
        delay(QD);
#pragma unroll 1
        for (int it = 0; it < SPIN_LIMIT; it++) {
            v = ld_poll4(pq);
            if (tagged(v, tag)) break;
        }
        *reinterpret_cast<uint2*>(smem + SM_Q + warp * 272 + lane * 8) =
            make_uint2(__byte_perm(v.x, v.y, 0x7632), __byte_perm(v.z, v.w, 0x7632));
    }
    bar_sync(3, 256);
    if (tid == 0) STAMP(5);
    const int head = g & 3;
    float sc[4];
    {
        uint32_t qa[4][4];
#pragma unroll
        for (int i = 0; i < 4; i++) ldsm4(qa[i], sb + SM_Q + (lane & 3) * 272 + (4 * i + (lane >> 3)) * 16);
        mbar_wait(bars + 8 * (warp >> 1));
        if (tid == 224) STAMP(13);
        float c[4][4];
        const uint32_t kb = sb + SM_K + (warp >> 1) * 16384 + (32 * (warp & 1) + (lane & 7)) * 128;
#pragma unroll
        for (int n = 0; n < 4; n++) {
#pragma unroll
            for (int e = 0; e < 4; e++) c[n][e] = 0.f;
#pragma unroll
            for (int i = 0; i < 4; i++) {
                uint32_t b[4];
                ldsm4(b, kb + n * 1024 + (i >> 1) * 8192 + (((4 * (i & 1) + (lane >> 3)) ^ (lane & 7)) << 4));
                mma(c[n], qa[i][0], 0u, qa[i][1], 0u, b[0], b[1]);
                mma(c[n], qa[i][2], 0u, qa[i][3], 0u, b[2], b[3]);
            }
        }
        const bool up = g >= 4;
        const float scale = 0.08838834764831845f;
        sc[0] = bfr(bfr(up ? c[2][0] : c[0][0]) * scale);
        sc[1] = bfr(bfr(up ? c[2][1] : c[0][1]) * scale);
        sc[2] = bfr(bfr(up ? c[3][0] : c[1][0]) * scale);
        sc[3] = bfr(bfr(up ? c[3][1] : c[1][1]) * scale);
    }
    float mcta;
    {
        float m = fmaxf(fmaxf(sc[0], sc[1]), fmaxf(sc[2], sc[3]));
        m = fmaxf(m, __shfl_xor_sync(~0u, m, 1));
        m = fmaxf(m, __shfl_xor_sync(~0u, m, 2));
        m = fmaxf(m, __shfl_xor_sync(~0u, m, 16));
        if (t == 0 && g < 4) reinterpret_cast<float*>(smem + SM_MX)[g * 8 + warp] = m;
        bar_sync(3, 256);
        const float4 m0 = *reinterpret_cast<const float4*>(smem + SM_MX + head * 32);
        const float4 m1 = *reinterpret_cast<const float4*>(smem + SM_MX + head * 32 + 16);
        mcta = fmaxf(fmaxf(fmaxf(m0.x, m0.y), fmaxf(m0.z, m0.w)), fmaxf(fmaxf(m1.x, m1.y), fmaxf(m1.z, m1.w)));
        const float p0 = __expf(sc[0] - mcta), p1 = __expf(sc[1] - mcta), p2 = __expf(sc[2] - mcta), p3 = __expf(sc[3] - mcta);
        uint8_t* pp = smem + SM_P + head * 528 + (32 * warp + 16 * (g >> 2) + 2 * t) * 2;
        *reinterpret_cast<uint32_t*>(pp) = pack_bf(p0, p1);
        *reinterpret_cast<uint32_t*>(pp + 16) = pack_bf(p2, p3);
        float l = (p0 + p1) + (p2 + p3);
        l += __shfl_xor_sync(~0u, l, 1);
        l += __shfl_xor_sync(~0u, l, 2);
        l += __shfl_xor_sync(~0u, l, 16);
        if (t == 0 && g < 4) reinterpret_cast<float*>(smem + SM_SUM)[g * 8 + warp] = l;
        bar_sync(3, 256);
        if (warp == 0 && t == 0 && g < 4) {
            const float4 l0 = *reinterpret_cast<const float4*>(smem + SM_SUM + head * 32);
            const float4 l1 = *reinterpret_cast<const float4*>(smem + SM_SUM + head * 32 + 16);
            const float ls = ((l0.x + l0.y) + (l0.z + l0.w)) + ((l1.x + l1.y) + (l1.z + l1.w));
            st_pub2(pml, tagf(mcta, tag), tagf(ls, tag));
        }
    }
    if (tid == 0) STAMP(6);
    {
        float c0[4] = {0.f, 0.f, 0.f, 0.f}, c1[4] = {0.f, 0.f, 0.f, 0.f};
        const uint32_t pb = sb + SM_P + (lane & 3) * 528 + (lane >> 3) * 16;
        const uint32_t vb = sb + SM_V + (warp >> 2) * 8192 + lrow * 128 + (((2 * (warp & 3) + lch) ^ (lane & 7)) << 4);
#pragma unroll
        for (int i = 0; i < 4; i++) {
            uint32_t p0[4], p1[4], a[4][4];
            ldsm4(p0, pb + i * 128);
            ldsm4(p1, pb + i * 128 + 64);
            mbar_wait(bars + 32 + 8 * i);
#pragma unroll
            for (int s = 0; s < 4; s++) ldsm4t(a[s], vb + i * 16384 + s * 2048);
            mma(c0, a[0][0], a[0][1], a[0][2], a[0][3], p0[0], p0[1]);
            mma(c1, a[1][0], a[1][1], a[1][2], a[1][3], p0[2], p0[3]);
            mma(c0, a[2][0], a[2][1], a[2][2], a[2][3], p1[0], p1[1]);
            mma(c1, a[3][0], a[3][1], a[3][2], a[3][3], p1[2], p1[3]);
        }
        const bool up = t >= 2;
        const float v0 = up ? c0[2] + c1[2] : c0[0] + c1[0];
        const float v1 = up ? c0[3] + c1[3] : c0[1] + c1[1];
        st_pub1(po, tagf(v0, tag));
        st_pub1(po + 4 * 512, tagf(v1, tag));
        if (warp == 0) bar_arrive(7, 64);
    }
    if (tid == 0) STAMP(7);
    float y0[4] = {0.f, 0.f, 0.f, 0.f}, y1[4] = {0.f, 0.f, 0.f, 0.f};
    const uint32_t wofs = (warp >> 1) * 4096 + lrow * 128 + (((4 * (warp & 1) + lch) ^ (lane & 7)) << 4);
    if (has_ffn) {
        float c[4][4];
        const uint32_t base = sb + SM_G + (warp * 32 + lrow) * 64 + ((lch ^ ((lane >> 1) & 3)) << 4);
        const uint32_t x0 = rank ? xn[4] : xn[0], x1 = rank ? xn[5] : xn[1], x2 = rank ? xn[6] : xn[2], x3 = rank ? xn[7] : xn[3];
        cluster_wait();
#pragma unroll
        for (int m = 0; m < 4; m++) {
            uint32_t a[4], b[4];
            if (!(m & 1)) mbar_wait(bars + 64 + 4 * m);
            ldsm4t(a, (base ^ ((m & 1) << 5)) + (m >> 1) * 16384);
            ldsm4t(b, (base ^ ((m & 1) << 5)) + (m >> 1) * 16384 + 1024);
#pragma unroll
            for (int e = 0; e < 4; e++) c[m][e] = 0.f;
            mma(c[m], a[0], a[1], a[2], a[3], x0, x1);
            mma(c[m], b[0], b[1], b[2], b[3], x2, x3);
        }
        st_pair(sb + SM_PART2 + (rank * 8 + warp) * 256 + (8 * t + g) * 8, bars + 120,
                __float_as_uint(sel4(t, c[0][0], c[0][2], c[1][0], c[1][2])), __float_as_uint(sel4(t, c[2][0], c[2][2], c[3][0], c[3][2])));
        mbar_wait(bars + 120);
        float gs = 0.f, us = 0.f;
#pragma unroll
        for (int w = 0; w < 16; w++) {
            const float2 v = reinterpret_cast<const float2*>(smem + SM_PART2)[w * 32 + lane];
            gs += v.x;
            us += v.y;
        }
        gs = bfr(gs);
        const float hv = bfr(__fdividef(gs, 1.f + __expf(-gs))) * bfr(us);
        const uint32_t hp = pack_bf(hv, __shfl_down_sync(~0u, hv, 1));
        uint32_t hb[4];
#pragma unroll
        for (int i = 0; i < 4; i++) hb[i] = __shfl_sync(~0u, hp, 8 * i + 2 * t);
        mbar_wait(bars + 80);
#pragma unroll
        for (int s = 0; s < 2; s++) {
            uint32_t a[4], b[4];
            ldsm4t(a, sb + SM_D + s * 2048 + wofs);
            ldsm4t(b, sb + SM_D + s * 2048 + (wofs ^ 32));
            mma(y0, a[0], a[1], a[2], a[3], hb[2 * s], hb[2 * s + 1]);
            mma(y1, b[0], b[1], b[2], b[3], hb[2 * s], hb[2 * s + 1]);
        }
    }
    if (tid == 0) STAMP(8);
    mbar_wait(bars + 128);
    {
        uint32_t ob[8];
#pragma unroll
        for (int i = 0; i < 8; i++) ob[i] = *reinterpret_cast<const uint32_t*>(smem + SM_O + i * 16 + t * 4);
        __nv_bfloat16* po_ = out + ocol;
        asm volatile("" : "+l"(po_));
        float z0[4] = {0.f, 0.f, 0.f, 0.f}, z1[4] = {0.f, 0.f, 0.f, 0.f};
#pragma unroll
        for (int s = 0; s < 4; s++) {
            uint32_t a[4], b[4];
            if (!(s & 1)) mbar_wait(bars + 88 + 4 * s);
            if (s == 2 && lane == 0 && warp == 7) STAMP(9);
            ldsm4t(a, sb + SM_W + (s >> 1) * 16384 + (s & 1) * 2048 + wofs);
            ldsm4t(b, sb + SM_W + (s >> 1) * 16384 + (s & 1) * 2048 + (wofs ^ 32));
            mma((s & 1) ? z0 : y0, a[0], a[1], a[2], a[3], ob[2 * s], ob[2 * s + 1]);
            mma((s & 1) ? z1 : y1, b[0], b[1], b[2], b[3], ob[2 * s], ob[2 * s + 1]);
        }
        const unsigned long long f = to_fix(sel4(t, y0[0], y0[2], y1[0], y1[2]) + sel4(t, z0[0], z0[2], z1[0], z1[2]));
        if (lane == 0 && warp == 7) STAMP(10);
        const unsigned long long a = atomicAdd(pa, f) + (f - (NCTA / 2 + 1));
        const __nv_bfloat16 r = __float2bfloat16_rn(from_fix(a));
        if (((uint32_t)a & 255u) == 0) {
            asm volatile("st.global.u16 [%0], %1;" ::"l"(po_), "h"(__bfloat16_as_ushort(r)) : "memory");
            *pa = 0;
            if (ocol == 0) g_epoch = tag == TAGM ? 1u : tag + 1;
        }
    }
}

typedef CUresult (*EncodeFn)(CUtensorMap*, CUtensorMapDataType, cuuint32_t, void*, const cuuint64_t*, const cuuint64_t*,
                             const cuuint32_t*, const cuuint32_t*, CUtensorMapInterleave, CUtensorMapSwizzle,
                             CUtensorMapL2promotion, CUtensorMapFloatOOBfill);

void make_map(EncodeFn enc, CUtensorMap* m, void* p, uint64_t d0, uint64_t d1, uint64_t d2, uint64_t s1, uint64_t s2,
              uint32_t b0, uint32_t b1, uint32_t b2, CUtensorMapSwizzle sw) {
    cuuint64_t gd[3] = {d0, d1, d2};
    cuuint64_t gs[2] = {s1, s2};
    cuuint32_t bd[3] = {b0, b1, b2};
    cuuint32_t es[3] = {1, 1, 1};
    enc(m, CU_TENSOR_MAP_DATA_TYPE_BFLOAT16, 3, p, gd, gs, bd, es, CU_TENSOR_MAP_INTERLEAVE_NONE, sw,
        CU_TENSOR_MAP_L2_PROMOTION_L2_256B, CU_TENSOR_MAP_FLOAT_OOB_FILL_NONE);
}

}

extern "C" void kernel_launch(void* const* d_in, const int* in_sizes, int n_in, void* d_out, int out_size) {
    static EncodeFn enc = nullptr;
    if (!enc) {
        void* fn = nullptr;
        cudaDriverEntryPointQueryResult qr;
        cudaGetDriverEntryPoint("cuTensorMapEncodeTiled", &fn, cudaEnableDefault, &qr);
        enc = (EncodeFn)fn;
        cudaFuncSetAttribute(fused_decode_kernel, cudaFuncAttributeMaxDynamicSharedMemorySize, SM_TOTAL);
    }
    Maps m;
    make_map(enc, &m.m[0], d_in[1], 64, (uint64_t)HKV * SK, 2, DH * 2, 128, 64, 64, 2, CU_TENSOR_MAP_SWIZZLE_128B);
    make_map(enc, &m.m[1], d_in[2], 64, (uint64_t)HKV * SK, 2, DH * 2, 128, 64, 64, 2, CU_TENSOR_MAP_SWIZZLE_128B);
    make_map(enc, &m.m[2], d_in[6], FF, 256, 2, FF * 2, FF * 2 * 256, 32, 256, 1, CU_TENSOR_MAP_SWIZZLE_64B);
    make_map(enc, &m.m[3], d_in[7], FF, 256, 2, FF * 2, FF * 2 * 256, 32, 256, 1, CU_TENSOR_MAP_SWIZZLE_64B);
    make_map(enc, &m.m[4], d_in[8], 64, FF, 8, D_MODEL * 2, 128, 64, 32, 4, CU_TENSOR_MAP_SWIZZLE_128B);
    make_map(enc, &m.m[5], d_in[4], 64, 4096, 8, D_MODEL * 2, 128, 64, 32, 4, CU_TENSOR_MAP_SWIZZLE_128B);
    fused_decode_kernel<<<NCTA, NTHREADS, SM_TOTAL>>>((const __nv_bfloat16*)d_in[0], (const __nv_bfloat16*)d_in[3],
                                                      (__nv_bfloat16*)d_out, m);
}
```

```cpp
#include <cuda_runtime.h>
#include <cuda_bf16.h>
#include <cuda.h>
#include <stdint.h>

namespace {

constexpr int D_MODEL = 512, HKV = 8, SK = 65536, DH = 128, WIN = 4096, FF = 1792;
constexpr int NCTA = 128, NFFN = FF / 16, NTHREADS = 320;
constexpr unsigned long long DEP = 0xFFDE012345678ull;
constexpr int NFREE = 2;
constexpr int T_FIRST = 600, T_ALL = 672, T_FFN = 600, T_NOFFN = 1500;
constexpr int Q_DELAY = 2000, O_DELAY = 1700;
constexpr uint32_t TAGM = 7u;
constexpr int SPIN_LIMIT = 1 << 20;

constexpr int SM_W = 0;
constexpr int SM_K = 32768;
constexpr int SM_V = SM_K + 65536;
constexpr int SM_G = SM_V + 65536;
constexpr int SM_U = SM_G + 16384;
constexpr int SM_D = SM_U + 16384;
constexpr int SM_BAR = SM_D + 16384;
constexpr int SM_PART = SM_BAR + 256;
constexpr int SM_Q = SM_PART + 1024;
constexpr int SM_P = SM_Q + 1088;
constexpr int SM_MX = SM_P + 2112;
constexpr int SM_SUM = SM_MX + 128;
constexpr int SM_O = SM_SUM + 128;
constexpr int SM_PART2 = SM_O + 128;
constexpr int SM_TOTAL = SM_PART2 + 4096;

struct __align__(64) Maps { CUtensorMap m[6]; };

__device__ uint32_t g_epoch = 1;
__device__ __align__(128) uint32_t g_q[NCTA * 32];
__device__ __align__(128) uint32_t g_o[NCTA * 16 * 32];
__device__ __align__(128) uint2 g_ml[HKV * 4 * 16];
__device__ __align__(128) unsigned long long g_acc[D_MODEL / 8 * 32];

__device__ __forceinline__ void mbar_init(uint32_t a, int n) { asm volatile("mbarrier.init.shared::cta.b64 [%0], %1;" ::"r"(a), "r"(n) : "memory"); }
__device__ __forceinline__ void mbar_expect(uint32_t a, int bytes) {
    asm volatile("mbarrier.arrive.expect_tx.shared::cta.b64 _, [%0], %1;" ::"r"(a), "r"(bytes) : "memory");
}
__device__ __forceinline__ void mbar_wait(uint32_t a) {
    uint32_t ok;
    int it = 0;
#pragma unroll 1
    do {
        asm volatile("{\n.reg .pred p;\nmbarrier.try_wait.parity.shared::cta.b64 p, [%1], 0;\nselp.u32 %0, 1, 0, p;\n}"
                     : "=r"(ok) : "r"(a) : "memory");
    } while (!ok && ++it < 4096);
}
__device__ __forceinline__ void tma3d(uint32_t dst, const CUtensorMap* m, int c0, int c1, int c2, uint32_t bar) {
    asm volatile("cp.async.bulk.tensor.3d.shared::cluster.global.mbarrier::complete_tx::bytes [%0], [%1, {%3, %4, %5}], [%2];"
                 ::"r"(dst), "l"(m), "r"(bar), "r"(c0), "r"(c1), "r"(c2) : "memory");
}
__device__ __forceinline__ void st_pair(uint32_t dst, uint32_t bar, uint32_t a, uint32_t b) {
#pragma unroll
    for (int r = 0; r < 2; r++) {
        uint32_t d, m;
        asm("mapa.shared::cluster.u32 %0, %1, %2;" : "=r"(d) : "r"(dst), "r"(r));
        asm("mapa.shared::cluster.u32 %0, %1, %2;" : "=r"(m) : "r"(bar), "r"(r));
        asm volatile("st.async.weak.shared::cluster.mbarrier::complete_tx::bytes.v2.b32 [%0], {%1,%2}, [%3];"
                     ::"r"(d), "r"(a), "r"(b), "r"(m) : "memory");
    }
}
__device__ __forceinline__ void cluster_arrive() { asm volatile("barrier.cluster.arrive.relaxed.aligned;" ::: "memory"); }
__device__ __forceinline__ void cluster_wait() { asm volatile("barrier.cluster.wait.acquire.aligned;" ::: "memory"); }
__device__ __forceinline__ void bar_sync(int id, int n) { asm volatile("bar.sync %0, %1;" ::"r"(id), "r"(n) : "memory"); }
__device__ __forceinline__ void bar_arrive(int id, int n) { asm volatile("bar.arrive %0, %1;" ::"r"(id), "r"(n) : "memory"); }
__device__ __forceinline__ void ldsm4(uint32_t (&r)[4], uint32_t a) {
    asm volatile("ldmatrix.sync.aligned.m8n8.x4.shared.b16 {%0,%1,%2,%3}, [%4];"
                 : "=r"(r[0]), "=r"(r[1]), "=r"(r[2]), "=r"(r[3]) : "r"(a) : "memory");
}
__device__ __forceinline__ void ldsm4t(uint32_t (&r)[4], uint32_t a) {
    asm volatile("ldmatrix.sync.aligned.m8n8.x4.trans.shared.b16 {%0,%1,%2,%3}, [%4];"
                 : "=r"(r[0]), "=r"(r[1]), "=r"(r[2]), "=r"(r[3]) : "r"(a) : "memory");
}
__device__ __forceinline__ void mma(float (&c)[4], uint32_t a0, uint32_t a1, uint32_t a2, uint32_t a3, uint32_t b0, uint32_t b1) {
    asm volatile("mma.sync.aligned.m16n8k16.row.col.f32.bf16.bf16.f32 {%0,%1,%2,%3}, {%4,%5,%6,%7}, {%8,%9}, {%0,%1,%2,%3};"
                 : "+f"(c[0]), "+f"(c[1]), "+f"(c[2]), "+f"(c[3])
                 : "r"(a0), "r"(a1), "r"(a2), "r"(a3), "r"(b0), "r"(b1));
}
__device__ __forceinline__ uint4 ld_poll4(const void* p) {
    uint4 v;
    asm volatile("ld.relaxed.gpu.global.v4.u32 {%0,%1,%2,%3}, [%4];" : "=r"(v.x), "=r"(v.y), "=r"(v.z), "=r"(v.w) : "l"(p) : "memory");
    return v;
}
__device__ __forceinline__ uint2 ld_poll2(const void* p) {
    uint2 v;
    asm volatile("ld.relaxed.gpu.global.v2.u32 {%0,%1}, [%2];" : "=r"(v.x), "=r"(v.y) : "l"(p) : "memory");
    return v;
}
__device__ __forceinline__ void st_pub1(void* p, uint32_t v) { asm volatile("st.relaxed.gpu.global.u32 [%0], %1;" ::"l"(p), "r"(v) : "memory"); }
__device__ __forceinline__ void st_pub2(void* p, uint32_t a, uint32_t b) {
    asm volatile("st.relaxed.gpu.global.v2.u32 [%0], {%1,%2};" ::"l"(p), "r"(a), "r"(b) : "memory");
}
__device__ __forceinline__ bool tagged(uint4 v, uint32_t tag) { return (((v.x ^ tag) | (v.y ^ tag) | (v.z ^ tag) | (v.w ^ tag)) & TAGM) == 0; }
__device__ __forceinline__ void delay(uint32_t cycles) {
    uint32_t t0, t1;
    asm volatile("mov.u32 %0, %%clock;" : "=r"(t0));
    do { asm volatile("mov.u32 %0, %%clock;" : "=r"(t1)); } while (t1 - t0 < cycles);
}
__device__ __forceinline__ uint32_t now_ns() { uint32_t t; asm volatile("mov.u32 %0, %%globaltimer_lo;" : "=r"(t)); return t; }
__device__ __forceinline__ unsigned long long to_fix(float v) { return ((unsigned long long)__float2ll_rn(v * 68719476736.f) & ~255ull) | 1ull; }
__device__ __forceinline__ float from_fix(unsigned long long a) { return __ll2float_rn((long long)a) * (1.f / 68719476736.f); }
__device__ __forceinline__ uint32_t tagf(float f, uint32_t tag) { return (__float_as_uint(f) & ~TAGM) | tag; }
__device__ __forceinline__ float untag(uint32_t u) { return __uint_as_float(u & ~TAGM); }
__device__ __forceinline__ float bfr(float f) { return __bfloat162float(__float2bfloat16_rn(f)); }
__device__ __forceinline__ float bflo(uint32_t u) { return __uint_as_float(u << 16); }
__device__ __forceinline__ float bfhi(uint32_t u) { return __uint_as_float(u & 0xffff0000u); }
__device__ __forceinline__ uint32_t pack_bf(float lo, float hi) {
    __nv_bfloat162 v = __floats2bfloat162_rn(lo, hi);
    return *reinterpret_cast<uint32_t*>(&v);
}
__device__ __forceinline__ float sel4(int t, float a, float b, float c, float d) { return (t & 2) ? ((t & 1) ? d : c) : ((t & 1) ? b : a); }

__global__ void __cluster_dims__(2, 1, 1) __launch_bounds__(NTHREADS, 1)
fused_decode_kernel(const __nv_bfloat16* __restrict__ x, const __nv_bfloat16* __restrict__ wq,
                    __nv_bfloat16* __restrict__ out, const __grid_constant__ Maps maps) {
    extern __shared__ __align__(1024) uint8_t smem[];
    const uint32_t sb = (uint32_t)__cvta_generic_to_shared(smem);
    const int tid = threadIdx.x, lane = tid & 31;
    const int warp = tid >> 5;
    const int cta = blockIdx.x, h = cta >> 4, j = cta & 15, pair = cta >> 1, rank = cta & 1;
    const uint32_t bars = sb + SM_BAR;
    const bool has_ffn = cta < NFFN;

    if (warp == 8) {
        uint32_t due = now_ns() + T_FIRST + cta * T_ALL / NCTA;
        const int u = (!has_ffn && lane >= 8) ? lane + 3 : lane;
        if (lane == 0) {
#pragma unroll
            for (int i = 0; i < 17; i++)
                if (i < 13 || i > 14) mbar_init(bars + 8 * i, 1);
            mbar_expect(bars + 120, 4096);
            mbar_expect(bars + 128, 128);
        }
        asm volatile("fence.proxy.async.shared::cta;" ::: "memory");
        __syncwarp();
        const int mi = u < 8 ? (u >> 2) : min(u - 6, 5);
        const int c0 = (u == 8 || u == 9) ? pair * 32 : 0;
        const int c1 = u < 8 ? h * SK + (SK - WIN) + (u & 3) * 1024 + j * 64 : (u < 10 ? 0 : (u == 10 ? pair * 32 : pair * 64 + (u - 11) * 32));
        const int c2 = u < 8 ? 0 : (u < 10 ? rank : 4 * rank);
        const uint32_t dst = sb + (u < 11 ? SM_K + u * 16384 : SM_W + (u - 11) * 16384);
        const int n = has_ffn ? 13 : 10;
        asm volatile("fence.mbarrier_init.release.cluster;" ::: "memory");
        cluster_arrive();
        bar_arrive(1, 288);
#pragma unroll 1
        for (int i = 0; i < n; i++) {
            if (i == NFREE) bar_sync(5, 96);
            if (i == n - 2) {
                bar_sync(2, 288);
                asm volatile("fence.proxy.async.shared::cta;" ::: "memory");
            }
            if (i >= NFREE) mbar_wait(bars + 8 * (int)((DEP >> (48 - 4 * i)) & 15));
            for (int it = 0; it < 1024 && (int)(now_ns() - due) < 0; it++) {}
            due += (i < 7 || (i == 7 && has_ffn)) ? T_ALL : (has_ffn ? T_FFN : T_NOFFN);
            if (lane == i) {
                mbar_expect(bars + 8 * u, 16384);
                tma3d(dst, &maps.m[mi], c0, c1, c2, bars + 8 * u);
            }
            __syncwarp();
        }
        return;
    }
    if (warp == 9) {
        const uint32_t tag = __ldcg(&g_epoch);
        cluster_arrive();
        cluster_wait();
        {
            const uint2* pml = g_ml + (h * 16 + (lane >> 3)) * 4 + (j >> 2);
            const uint4* po = reinterpret_cast<const uint4*>(g_o + cta * 512) + lane;
            uint2 ml[4];
            uint4 v[4];
            bar_sync(7, 64);
            delay(O_DELAY);
#pragma unroll
            for (int i = 0; i < 4; i++) ml[i] = ld_poll2(pml + 16 * i);
#pragma unroll
            for (int i = 0; i < 4; i++) v[i] = ld_poll4(po + 32 * i);
#pragma unroll 1
            for (int it = 0; it < SPIN_LIMIT; it++) {
                bool ok = true;
#pragma unroll
                for (int i = 0; i < 4; i++) {
                    if (!tagged(v[i], tag)) { v[i] = ld_poll4(po + 32 * i); ok = false; }
                    if (((ml[i].x ^ tag) | (ml[i].y ^ tag)) & TAGM) { ml[i] = ld_poll2(pml + 16 * i); ok = false; }
                }
                if (__all_sync(~0u, ok)) break;
            }
            float M = fmaxf(fmaxf(untag(ml[0].x), untag(ml[1].x)), fmaxf(untag(ml[2].x), untag(ml[3].x)));
            M = fmaxf(M, __shfl_xor_sync(~0u, M, 8));
            M = fmaxf(M, __shfl_xor_sync(~0u, M, 16));
            float a0 = 0.f, a1 = 0.f, a2 = 0.f, a3 = 0.f, L = 0.f;
#pragma unroll
            for (int i = 0; i < 4; i++) {
                const float w = __expf(untag(ml[i].x) - M);
                L += w * untag(ml[i].y);
                a0 += w * untag(v[i].x); a1 += w * untag(v[i].y);
                a2 += w * untag(v[i].z); a3 += w * untag(v[i].w);
            }
#pragma unroll
            for (int s = 8; s < 32; s <<= 1) {
                L += __shfl_xor_sync(~0u, L, s);
                a0 += __shfl_xor_sync(~0u, a0, s); a1 += __shfl_xor_sync(~0u, a1, s);
                a2 += __shfl_xor_sync(~0u, a2, s); a3 += __shfl_xor_sync(~0u, a3, s);
            }
            L = __fdividef(1.f, L);
            if (lane < 8) st_pair(sb + SM_O + rank * 64 + lane * 8, bars + 128, pack_bf(a0 * L, a1 * L), pack_bf(a2 * L, a3 * L));
        }
        return;
    }

    const int g = lane >> 2, t = lane & 3;
    const int lrow = (lane & 7) + ((lane >> 4) << 3);
    const int lch = (lane >> 3) & 1;
    {
        const uint32_t ofs = (warp * 32 + g) * 8192 + cta * 64 + t * 16;
        const uint32_t dst = sb + SM_W + (warp * 64 + g) * 64 + ((t ^ ((g >> 1) & 3)) << 4);
        const char* src = reinterpret_cast<const char*>(wq) + ofs;
#pragma unroll
        for (int i = 0; i < 8; i++)
            asm volatile("cp.async.cg.shared.global.L2::128B [%0], [%1], 16;" ::"r"(dst + i * 512), "l"(src + (size_t)((i >> 2) * 32 + (i & 3)) * 65536) : "memory");
        if ((warp & 3) == 3) {
            const uint32_t b = bars + 8 * (13 + (warp >> 2));
            if (lane == 0) mbar_init(b, 32);
            __syncwarp();
            asm volatile("cp.async.mbarrier.arrive.noinc.shared::cta.b64 [%0];" ::"r"(b) : "memory");
            bar_arrive(5, 96);
        }
    }
    cluster_arrive();
    uint32_t xn[8];
    uint32_t* const pqo = g_q + cta * 32 + lane;
    uint2* const pml = g_ml + cta * 4 + (g & 3);
    uint32_t* const po = g_o + ((h * 16 + (t & 1) * 8 + (warp >> 1)) * 16 + j) * 32 + (warp & 1) * 16 + (t >> 1) * 8 + g;
    unsigned long long* const pa = g_acc + (rank * 32 + (tid >> 3)) * 32 + (tid & 7);
    const int ocol = 256 * rank + 32 * warp + 8 * t + g;
    const uint32_t tag = __ldcg(&g_epoch);
    {
        const uint4 xa = __ldg(reinterpret_cast<const uint4*>(x) + lane);
        const uint4 xb = __ldg(reinterpret_cast<const uint4*>(x) + 32 + lane);
#pragma unroll
        for (int i = 0; i < 8; i++) xn[i] = __ldg(reinterpret_cast<const uint32_t*>(x) + (i >> 2) * 128 + warp * 16 + (i & 3) * 4 + t);
        if (pair == (tid >> 2)) atomicAdd(pa, to_fix(__bfloat162float(x[ocol])));
        const uint32_t xw[8] = {xa.x, xa.y, xa.z, xa.w, xb.x, xb.y, xb.z, xb.w};
        float s = 0.f;
#pragma unroll
        for (int i = 0; i < 8; i++) s += bflo(xw[i]) + bfhi(xw[i]);
#pragma unroll
        for (int o = 1; o < 32; o <<= 1) s += __shfl_xor_sync(~0u, s, o);
        const float mean = s * (1.f / D_MODEL);
        float q = 0.f;
#pragma unroll
        for (int i = 0; i < 8; i++) {
            const float a = bflo(xw[i]) - mean, b = bfhi(xw[i]) - mean;
            q += a * a + b * b;
        }
#pragma unroll
        for (int o = 1; o < 32; o <<= 1) q += __shfl_xor_sync(~0u, q, o);
        const float mb = bfr(mean);
        float sd;
        asm("sqrt.approx.f32 %0, %1;" : "=f"(sd) : "f"(bfr(bfr(q * (1.f / D_MODEL)) + 1e-5f)));
        const float rden = __fdividef(1.f, bfr(sd));
#pragma unroll
        for (int i = 0; i < 8; i++) xn[i] = pack_bf(bfr(bflo(xn[i]) - mb) * rden, bfr(bfhi(xn[i]) - mb) * rden);
    }
    asm volatile("cp.async.wait_all;" ::: "memory");
    __syncwarp();
    {
        float c0[4] = {0.f, 0.f, 0.f, 0.f}, c1[4] = {0.f, 0.f, 0.f, 0.f};
        const uint32_t base = sb + SM_W + (warp * 64 + lrow) * 64;
        const int sw = (lane >> 1) & 3;
#pragma unroll
        for (int s = 0; s < 4; s++) {
            uint32_t a[4], b[4];
            ldsm4t(a, base + s * 1024 + ((lch ^ sw) << 4));
            ldsm4t(b, base + s * 1024 + (((2 + lch) ^ sw) << 4));
            mma(c0, a[0], a[1], a[2], a[3], xn[2 * s], xn[2 * s + 1]);
            mma(c1, b[0], b[1], b[2], b[3], xn[2 * s], xn[2 * s + 1]);
        }
        reinterpret_cast<float*>(smem + SM_PART)[warp * 32 + 8 * t + g] = sel4(t, c0[0], c0[2], c1[0], c1[2]);
    }
    bar_arrive(2, 288);
    bar_sync(1, 288);
    if (warp == 0) {
        float s = 0.f;
#pragma unroll
        for (int w = 0; w < 8; w++) s += reinterpret_cast<const float*>(smem + SM_PART)[w * 32 + lane];
        st_pub1(pqo, __float_as_uint(bfr(s)) | tag);
    }
    if (tid < 128) {
        const uint4* pq = reinterpret_cast<const uint4*>(g_q + h * 512) + tid;
        uint4 v;
        delay(Q_DELAY);
#pragma unroll 1
        for (int it = 0; it < SPIN_LIMIT; it++) {
            v = ld_poll4(pq);
            if (tagged(v, tag)) break;
        }
        *reinterpret_cast<uint2*>(smem + SM_Q + warp * 272 + lane * 8) =
            make_uint2(__byte_perm(v.x, v.y, 0x7632), __byte_perm(v.z, v.w, 0x7632));
    }
    bar_sync(3, 256);
    const int head = g & 3;
    float sc[4];
    {
        uint32_t qa[4][4];
#pragma unroll
        for (int i = 0; i < 4; i++) ldsm4(qa[i], sb + SM_Q + (lane & 3) * 272 + (4 * i + (lane >> 3)) * 16);
        mbar_wait(bars + 8 * (warp >> 1));
        float c[4][4];
        const uint32_t kb = sb + SM_K + (warp >> 1) * 16384 + (32 * (warp & 1) + (lane & 7)) * 128;
#pragma unroll
        for (int n = 0; n < 4; n++) {
#pragma unroll
            for (int e = 0; e < 4; e++) c[n][e] = 0.f;
#pragma unroll
            for (int i = 0; i < 4; i++) {
                uint32_t b[4];
                ldsm4(b, kb + n * 1024 + (i >> 1) * 8192 + (((4 * (i & 1) + (lane >> 3)) ^ (lane & 7)) << 4));
                mma(c[n], qa[i][0], 0u, qa[i][1], 0u, b[0], b[1]);
                mma(c[n], qa[i][2], 0u, qa[i][3], 0u, b[2], b[3]);
            }
        }
        const bool up = g >= 4;
        const float scale = 0.08838834764831845f;
        sc[0] = bfr(bfr(up ? c[2][0] : c[0][0]) * scale);
        sc[1] = bfr(bfr(up ? c[2][1] : c[0][1]) * scale);
        sc[2] = bfr(bfr(up ? c[3][0] : c[1][0]) * scale);
        sc[3] = bfr(bfr(up ? c[3][1] : c[1][1]) * scale);
    }
    float mcta;
    {
        float m = fmaxf(fmaxf(sc[0], sc[1]), fmaxf(sc[2], sc[3]));
        m = fmaxf(m, __shfl_xor_sync(~0u, m, 1));
        m = fmaxf(m, __shfl_xor_sync(~0u, m, 2));
        m = fmaxf(m, __shfl_xor_sync(~0u, m, 16));
        if (t == 0 && g < 4) reinterpret_cast<float*>(smem + SM_MX)[g * 8 + warp] = m;
        bar_sync(3, 256);
        const float4 m0 = *reinterpret_cast<const float4*>(smem + SM_MX + head * 32);
        const float4 m1 = *reinterpret_cast<const float4*>(smem + SM_MX + head * 32 + 16);
        mcta = fmaxf(fmaxf(fmaxf(m0.x, m0.y), fmaxf(m0.z, m0.w)), fmaxf(fmaxf(m1.x, m1.y), fmaxf(m1.z, m1.w)));
        const float p0 = __expf(sc[0] - mcta), p1 = __expf(sc[1] - mcta), p2 = __expf(sc[2] - mcta), p3 = __expf(sc[3] - mcta);
        uint8_t* pp = smem + SM_P + head * 528 + (32 * warp + 16 * (g >> 2) + 2 * t) * 2;
        *reinterpret_cast<uint32_t*>(pp) = pack_bf(p0, p1);
        *reinterpret_cast<uint32_t*>(pp + 16) = pack_bf(p2, p3);
        float l = (p0 + p1) + (p2 + p3);
        l += __shfl_xor_sync(~0u, l, 1);
        l += __shfl_xor_sync(~0u, l, 2);
        l += __shfl_xor_sync(~0u, l, 16);
        if (t == 0 && g < 4) reinterpret_cast<float*>(smem + SM_SUM)[g * 8 + warp] = l;
        bar_sync(3, 256);
        if (warp == 0 && t == 0 && g < 4) {
            const float4 l0 = *reinterpret_cast<const float4*>(smem + SM_SUM + head * 32);
            const float4 l1 = *reinterpret_cast<const float4*>(smem + SM_SUM + head * 32 + 16);
            const float ls = ((l0.x + l0.y) + (l0.z + l0.w)) + ((l1.x + l1.y) + (l1.z + l1.w));
            st_pub2(pml, tagf(mcta, tag), tagf(ls, tag));
        }
    }
    {
        float c0[4] = {0.f, 0.f, 0.f, 0.f}, c1[4] = {0.f, 0.f, 0.f, 0.f};
        const uint32_t pb = sb + SM_P + (lane & 3) * 528 + (lane >> 3) * 16;
        const uint32_t vb = sb + SM_V + (warp >> 2) * 8192 + lrow * 128 + (((2 * (warp & 3) + lch) ^ (lane & 7)) << 4);
#pragma unroll
        for (int i = 0; i < 4; i++) {
            uint32_t p0[4], p1[4], a[4][4];
            ldsm4(p0, pb + i * 128);
            ldsm4(p1, pb + i * 128 + 64);
            mbar_wait(bars + 32 + 8 * i);
#pragma unroll
            for (int s = 0; s < 4; s++) ldsm4t(a[s], vb + i * 16384 + s * 2048);
            mma(c0, a[0][0], a[0][1], a[0][2], a[0][3], p0[0], p0[1]);
            mma(c1, a[1][0], a[1][1], a[1][2], a[1][3], p0[2], p0[3]);
            mma(c0, a[2][0], a[2][1], a[2][2], a[2][3], p1[0], p1[1]);
            mma(c1, a[3][0], a[3][1], a[3][2], a[3][3], p1[2], p1[3]);
        }
        const bool up = t >= 2;
        const float v0 = up ? c0[2] + c1[2] : c0[0] + c1[0];
        const float v1 = up ? c0[3] + c1[3] : c0[1] + c1[1];
        st_pub1(po, tagf(v0, tag));
        st_pub1(po + 4 * 512, tagf(v1, tag));
        if (warp == 0) bar_arrive(7, 64);
    }
    float y0[4] = {0.f, 0.f, 0.f, 0.f}, y1[4] = {0.f, 0.f, 0.f, 0.f};
    const uint32_t wofs = (warp >> 1) * 4096 + lrow * 128 + (((4 * (warp & 1) + lch) ^ (lane & 7)) << 4);
    if (has_ffn) {
        float c[4][4];
        const uint32_t base = sb + SM_G + (warp * 32 + lrow) * 64 + ((lch ^ ((lane >> 1) & 3)) << 4);
        const uint32_t x0 = rank ? xn[4] : xn[0], x1 = rank ? xn[5] : xn[1], x2 = rank ? xn[6] : xn[2], x3 = rank ? xn[7] : xn[3];
        cluster_wait();
#pragma unroll
        for (int m = 0; m < 4; m++) {
            uint32_t a[4], b[4];
            if (!(m & 1)) mbar_wait(bars + 64 + 4 * m);
            ldsm4t(a, (base ^ ((m & 1) << 5)) + (m >> 1) * 16384);
            ldsm4t(b, (base ^ ((m & 1) << 5)) + (m >> 1) * 16384 + 1024);
#pragma unroll
            for (int e = 0; e < 4; e++) c[m][e] = 0.f;
            mma(c[m], a[0], a[1], a[2], a[3], x0, x1);
            mma(c[m], b[0], b[1], b[2], b[3], x2, x3);
        }
        st_pair(sb + SM_PART2 + (rank * 8 + warp) * 256 + (8 * t + g) * 8, bars + 120,
                __float_as_uint(sel4(t, c[0][0], c[0][2], c[1][0], c[1][2])), __float_as_uint(sel4(t, c[2][0], c[2][2], c[3][0], c[3][2])));
        mbar_wait(bars + 120);
        float gs = 0.f, us = 0.f;
#pragma unroll
        for (int w = 0; w < 16; w++) {
            const float2 v = reinterpret_cast<const float2*>(smem + SM_PART2)[w * 32 + lane];
            gs += v.x;
            us += v.y;
        }
        gs = bfr(gs);
        const float hv = bfr(__fdividef(gs, 1.f + __expf(-gs))) * bfr(us);
        const uint32_t hp = pack_bf(hv, __shfl_down_sync(~0u, hv, 1));
        uint32_t hb[4];
#pragma unroll
        for (int i = 0; i < 4; i++) hb[i] = __shfl_sync(~0u, hp, 8 * i + 2 * t);
        mbar_wait(bars + 80);
#pragma unroll
        for (int s = 0; s < 2; s++) {
            uint32_t a[4], b[4];
            ldsm4t(a, sb + SM_D + s * 2048 + wofs);
            ldsm4t(b, sb + SM_D + s * 2048 + (wofs ^ 32));
            mma(y0, a[0], a[1], a[2], a[3], hb[2 * s], hb[2 * s + 1]);
            mma(y1, b[0], b[1], b[2], b[3], hb[2 * s], hb[2 * s + 1]);
        }
    }
    mbar_wait(bars + 128);
    {
        uint32_t ob[8];
#pragma unroll
        for (int i = 0; i < 8; i++) ob[i] = *reinterpret_cast<const uint32_t*>(smem + SM_O + i * 16 + t * 4);
        float z0[4] = {0.f, 0.f, 0.f, 0.f}, z1[4] = {0.f, 0.f, 0.f, 0.f};
#pragma unroll
        for (int s = 0; s < 4; s++) {
            uint32_t a[4], b[4];
            if (!(s & 1)) mbar_wait(bars + 88 + 4 * s);
            ldsm4t(a, sb + SM_W + (s >> 1) * 16384 + (s & 1) * 2048 + wofs);
            ldsm4t(b, sb + SM_W + (s >> 1) * 16384 + (s & 1) * 2048 + (wofs ^ 32));
            mma((s & 1) ? z0 : y0, a[0], a[1], a[2], a[3], ob[2 * s], ob[2 * s + 1]);
            mma((s & 1) ? z1 : y1, b[0], b[1], b[2], b[3], ob[2 * s], ob[2 * s + 1]);
        }
        const unsigned long long f = to_fix(sel4(t, y0[0], y0[2], y1[0], y1[2]) + sel4(t, z0[0], z0[2], z1[0], z1[2]));
        const unsigned long long a = atomicAdd(pa, f) + (f - (NCTA / 2 + 1));
        if (((uint32_t)a & 255u) == 0) {
            out[ocol] = __float2bfloat16_rn(from_fix(a));
            *pa = 0;
            if (ocol == 0) g_epoch = tag == TAGM ? 1u : tag + 1;
        }
    }
}

typedef CUresult (*EncodeFn)(CUtensorMap*, CUtensorMapDataType, cuuint32_t, void*, const cuuint64_t*, const cuuint64_t*,
                             const cuuint32_t*, const cuuint32_t*, CUtensorMapInterleave, CUtensorMapSwizzle,
                             CUtensorMapL2promotion, CUtensorMapFloatOOBfill);

void make_map(EncodeFn enc, CUtensorMap* m, void* p, uint64_t d0, uint64_t d1, uint64_t d2, uint64_t s1, uint64_t s2,
              uint32_t b0, uint32_t b1, uint32_t b2, CUtensorMapSwizzle sw) {
    cuuint64_t gd[3] = {d0, d1, d2};
    cuuint64_t gs[2] = {s1, s2};
    cuuint32_t bd[3] = {b0, b1, b2};
    cuuint32_t es[3] = {1, 1, 1};
    enc(m, CU_TENSOR_MAP_DATA_TYPE_BFLOAT16, 3, p, gd, gs, bd, es, CU_TENSOR_MAP_INTERLEAVE_NONE, sw,
        CU_TENSOR_MAP_L2_PROMOTION_L2_128B, CU_TENSOR_MAP_FLOAT_OOB_FILL_NONE);
}

}

extern "C" void kernel_launch(void* const* d_in, const int* in_sizes, int n_in, void* d_out, int out_size) {
    static EncodeFn enc = nullptr;
    if (!enc) {
        void* fn = nullptr;
        cudaDriverEntryPointQueryResult qr;
        cudaGetDriverEntryPoint("cuTensorMapEncodeTiled", &fn, cudaEnableDefault, &qr);
        enc = (EncodeFn)fn;
        cudaFuncSetAttribute(fused_decode_kernel, cudaFuncAttributeMaxDynamicSharedMemorySize, SM_TOTAL);
    }
    Maps m;
    make_map(enc, &m.m[0], d_in[1], 64, (uint64_t)HKV * SK, 2, DH * 2, 128, 64, 64, 2, CU_TENSOR_MAP_SWIZZLE_128B);
    make_map(enc, &m.m[1], d_in[2], 64, (uint64_t)HKV * SK, 2, DH * 2, 128, 64, 64, 2, CU_TENSOR_MAP_SWIZZLE_128B);
    make_map(enc, &m.m[2], d_in[6], FF, 256, 2, FF * 2, FF * 2 * 256, 32, 256, 1, CU_TENSOR_MAP_SWIZZLE_64B);
    make_map(enc, &m.m[3], d_in[7], FF, 256, 2, FF * 2, FF * 2 * 256, 32, 256, 1, CU_TENSOR_MAP_SWIZZLE_64B);
    make_map(enc, &m.m[4], d_in[8], 64, FF, 8, D_MODEL * 2, 128, 64, 32, 4, CU_TENSOR_MAP_SWIZZLE_128B);
    make_map(enc, &m.m[5], d_in[4], 64, 4096, 8, D_MODEL * 2, 128, 64, 32, 4, CU_TENSOR_MAP_SWIZZLE_128B);
    fused_decode_kernel<<<NCTA, NTHREADS, SM_TOTAL>>>((const __nv_bfloat16*)d_in[0], (const __nv_bfloat16*)d_in[3],
                                                      (__nv_bfloat16*)d_out, m);
}
```

```cpp
#include <cuda_runtime.h>
#include <cuda_bf16.h>
#include <cuda.h>
#include <stdint.h>

namespace {

constexpr int D_MODEL = 512, HKV = 8, SK = 65536, DH = 128, WIN = 4096, FF = 1792;
constexpr int NCTA = 128, NFFN = FF / 16, NTHREADS = 320;
constexpr unsigned long long DEP = 0xFFDE012345678ull;
constexpr int NFREE = 2;
constexpr int T_FIRST = 600, T_ALL = 672, T_FFN = 600, T_NOFFN = 1500;
constexpr int Q_DELAY = 2000, O_DELAY = 1700;
constexpr uint32_t TAGM = 7u;
constexpr int SPIN_LIMIT = 1 << 20;

constexpr int SM_W = 0;
constexpr int SM_K = 32768;
constexpr int SM_V = SM_K + 65536;
constexpr int SM_G = SM_V + 65536;
constexpr int SM_U = SM_G + 16384;
constexpr int SM_D = SM_U + 16384;
constexpr int SM_BAR = SM_D + 16384;
constexpr int SM_PART = SM_BAR + 256;
constexpr int SM_Q = SM_PART + 1024;
constexpr int SM_P = SM_Q + 1088;
constexpr int SM_MX = SM_P + 2112;
constexpr int SM_SUM = SM_MX + 128;
constexpr int SM_O = SM_SUM + 128;
constexpr int SM_PART2 = SM_O + 128;
constexpr int SM_TOTAL = SM_PART2 + 4096;

struct __align__(64) Maps { CUtensorMap m[6]; };

__device__ uint32_t g_epoch = 1;
__device__ __align__(128) uint32_t g_q[NCTA * 32];
__device__ __align__(128) uint32_t g_o[NCTA * 16 * 32];
__device__ __align__(128) uint2 g_ml[HKV * 4 * 16];
__device__ __align__(128) unsigned long long g_acc[D_MODEL / 8 * 32];

__device__ __forceinline__ void mbar_init(uint32_t a, int n) { asm volatile("mbarrier.init.shared::cta.b64 [%0], %1;" ::"r"(a), "r"(n) : "memory"); }
__device__ __forceinline__ void mbar_expect(uint32_t a, int bytes) {
    asm volatile("mbarrier.arrive.expect_tx.shared::cta.b64 _, [%0], %1;" ::"r"(a), "r"(bytes) : "memory");
}
__device__ __forceinline__ void mbar_wait(uint32_t a) {
    uint32_t ok;
    int it = 0;
#pragma unroll 1
    do {
        asm volatile("{\n.reg .pred p;\nmbarrier.try_wait.parity.shared::cta.b64 p, [%1], 0;\nselp.u32 %0, 1, 0, p;\n}"
                     : "=r"(ok) : "r"(a) : "memory");
    } while (!ok && ++it < 4096);
}
__device__ __forceinline__ void tma3d(uint32_t dst, const CUtensorMap* m, int c0, int c1, int c2, uint32_t bar) {
    asm volatile("cp.async.bulk.tensor.3d.shared::cluster.global.mbarrier::complete_tx::bytes [%0], [%1, {%3, %4, %5}], [%2];"
                 ::"r"(dst), "l"(m), "r"(bar), "r"(c0), "r"(c1), "r"(c2) : "memory");
}
__device__ __forceinline__ void st_pair(uint32_t dst, uint32_t bar, uint32_t a, uint32_t b) {
#pragma unroll
    for (int r = 0; r < 2; r++) {
        uint32_t d, m;
        asm("mapa.shared::cluster.u32 %0, %1, %2;" : "=r"(d) : "r"(dst), "r"(r));
        asm("mapa.shared::cluster.u32 %0, %1, %2;" : "=r"(m) : "r"(bar), "r"(r));
        asm volatile("st.async.weak.shared::cluster.mbarrier::complete_tx::bytes.v2.b32 [%0], {%1,%2}, [%3];"
                     ::"r"(d), "r"(a), "r"(b), "r"(m) : "memory");
    }
}
__device__ __forceinline__ void cluster_arrive() { asm volatile("barrier.cluster.arrive.relaxed.aligned;" ::: "memory"); }
__device__ __forceinline__ void cluster_wait() { asm volatile("barrier.cluster.wait.acquire.aligned;" ::: "memory"); }
__device__ __forceinline__ void bar_sync(int id, int n) { asm volatile("bar.sync %0, %1;" ::"r"(id), "r"(n) : "memory"); }
__device__ __forceinline__ void bar_arrive(int id, int n) { asm volatile("bar.arrive %0, %1;" ::"r"(id), "r"(n) : "memory"); }
__device__ __forceinline__ void ldsm4(uint32_t (&r)[4], uint32_t a) {
    asm volatile("ldmatrix.sync.aligned.m8n8.x4.shared.b16 {%0,%1,%2,%3}, [%4];"
                 : "=r"(r[0]), "=r"(r[1]), "=r"(r[2]), "=r"(r[3]) : "r"(a) : "memory");
}
__device__ __forceinline__ void ldsm4t(uint32_t (&r)[4], uint32_t a) {
    asm volatile("ldmatrix.sync.aligned.m8n8.x4.trans.shared.b16 {%0,%1,%2,%3}, [%4];"
                 : "=r"(r[0]), "=r"(r[1]), "=r"(r[2]), "=r"(r[3]) : "r"(a) : "memory");
}
__device__ __forceinline__ void mma(float (&c)[4], uint32_t a0, uint32_t a1, uint32_t a2, uint32_t a3, uint32_t b0, uint32_t b1) {
    asm volatile("mma.sync.aligned.m16n8k16.row.col.f32.bf16.bf16.f32 {%0,%1,%2,%3}, {%4,%5,%6,%7}, {%8,%9}, {%0,%1,%2,%3};"
                 : "+f"(c[0]), "+f"(c[1]), "+f"(c[2]), "+f"(c[3])
                 : "r"(a0), "r"(a1), "r"(a2), "r"(a3), "r"(b0), "r"(b1));
}
__device__ __forceinline__ uint4 ld_poll4(const void* p) {
    uint4 v;
    asm volatile("ld.relaxed.gpu.global.v4.u32 {%0,%1,%2,%3}, [%4];" : "=r"(v.x), "=r"(v.y), "=r"(v.z), "=r"(v.w) : "l"(p) : "memory");
    return v;
}
__device__ __forceinline__ uint2 ld_poll2(const void* p) {
    uint2 v;
    asm volatile("ld.relaxed.gpu.global.v2.u32 {%0,%1}, [%2];" : "=r"(v.x), "=r"(v.y) : "l"(p) : "memory");
    return v;
}
__device__ __forceinline__ void st_pub1(void* p, uint32_t v) { asm volatile("st.relaxed.gpu.global.u32 [%0], %1;" ::"l"(p), "r"(v) : "memory"); }
__device__ __forceinline__ void st_pub2(void* p, uint32_t a, uint32_t b) {
    asm volatile("st.relaxed.gpu.global.v2.u32 [%0], {%1,%2};" ::"l"(p), "r"(a), "r"(b) : "memory");
}
__device__ __forceinline__ bool tagged(uint4 v, uint32_t tag) { return (((v.x ^ tag) | (v.y ^ tag) | (v.z ^ tag) | (v.w ^ tag)) & TAGM) == 0; }
__device__ __forceinline__ void delay(uint32_t cycles) {
    uint32_t t0, t1;
    asm volatile("mov.u32 %0, %%clock;" : "=r"(t0));
    do { asm volatile("mov.u32 %0, %%clock;" : "=r"(t1)); } while (t1 - t0 < cycles);
}
__device__ __forceinline__ uint32_t now_ns() { uint32_t t; asm volatile("mov.u32 %0, %%globaltimer_lo;" : "=r"(t)); return t; }
__device__ __forceinline__ unsigned long long to_fix(float v) { return ((unsigned long long)__float2ll_rn(v * 68719476736.f) & ~255ull) | 1ull; }
__device__ __forceinline__ float from_fix(unsigned long long a) { return __ll2float_rn((long long)a) * (1.f / 68719476736.f); }
__device__ __forceinline__ uint32_t tagf(float f, uint32_t tag) { return (__float_as_uint(f) & ~TAGM) | tag; }
__device__ __forceinline__ float untag(uint32_t u) { return __uint_as_float(u & ~TAGM); }
__device__ __forceinline__ float bfr(float f) { return __bfloat162float(__float2bfloat16_rn(f)); }
__device__ __forceinline__ float bflo(uint32_t u) { return __uint_as_float(u << 16); }
__device__ __forceinline__ float bfhi(uint32_t u) { return __uint_as_float(u & 0xffff0000u); }
__device__ __forceinline__ uint32_t pack_bf(float lo, float hi) {
    __nv_bfloat162 v = __floats2bfloat162_rn(lo, hi);
    return *reinterpret_cast<uint32_t*>(&v);
}
__device__ __forceinline__ float sel4(int t, float a, float b, float c, float d) { return (t & 2) ? ((t & 1) ? d : c) : ((t & 1) ? b : a); }

__global__ void __cluster_dims__(2, 1, 1) __launch_bounds__(NTHREADS, 1)
fused_decode_kernel(const __nv_bfloat16* __restrict__ x, const __nv_bfloat16* __restrict__ wq,
                    __nv_bfloat16* __restrict__ out, const __grid_constant__ Maps maps) {
    extern __shared__ __align__(1024) uint8_t smem[];
    const uint32_t sb = (uint32_t)__cvta_generic_to_shared(smem);
    const int tid = threadIdx.x, lane = tid & 31;
    const int warp = tid >> 5;
    const int cta = blockIdx.x, h = cta >> 4, j = cta & 15, pair = cta >> 1, rank = cta & 1;
    const uint32_t bars = sb + SM_BAR;
    const bool has_ffn = cta < NFFN;

    if (warp == 8) {
        uint32_t due = now_ns() + T_FIRST + cta * T_ALL / NCTA;
        const int u = (!has_ffn && lane >= 8) ? lane + 3 : lane;
        if (lane == 0) {
#pragma unroll
            for (int i = 0; i < 17; i++)
                if (i < 13 || i > 14) mbar_init(bars + 8 * i, 1);
            mbar_expect(bars + 120, 4096);
            mbar_expect(bars + 128, 128);
        }
        asm volatile("fence.proxy.async.shared::cta;" ::: "memory");
        __syncwarp();
        const int mi = u < 8 ? (u >> 2) : min(u - 6, 5);
        const int c0 = (u == 8 || u == 9) ? pair * 32 : 0;
        const int c1 = u < 8 ? h * SK + (SK - WIN) + (u & 3) * 1024 + j * 64 : (u < 10 ? 0 : (u == 10 ? pair * 32 : pair * 64 + (u - 11) * 32));
        const int c2 = u < 8 ? 0 : (u < 10 ? rank : 4 * rank);
        const uint32_t dst = sb + (u < 11 ? SM_K + u * 16384 : SM_W + (u - 11) * 16384);
        const int n = has_ffn ? 13 : 10;
        asm volatile("fence.mbarrier_init.release.cluster;" ::: "memory");
        cluster_arrive();
        bar_arrive(1, 288);
#pragma unroll 1
        for (int i = 0; i < n; i++) {
            if (i == NFREE) bar_sync(5, 96);
            if (i == n - 2) {
                bar_sync(2, 288);
                asm volatile("fence.proxy.async.shared::cta;" ::: "memory");
            }
            if (i >= NFREE) mbar_wait(bars + 8 * (int)((DEP >> (48 - 4 * i)) & 15));
            for (int it = 0; it < 1024 && (int)(now_ns() - due) < 0; it++) {}
            due += (i < 7 || (i == 7 && has_ffn)) ? T_ALL : (has_ffn ? T_FFN : T_NOFFN);
            if (lane == i) {
                mbar_expect(bars + 8 * u, 16384);
                tma3d(dst, &maps.m[mi], c0, c1, c2, bars + 8 * u);
            }
            __syncwarp();
        }
        return;
    }
    if (warp == 9) {
        const uint32_t tag = __ldcg(&g_epoch);
        cluster_arrive();
        cluster_wait();
        {
            const uint2* pml = g_ml + (h * 16 + (lane >> 3)) * 4 + (j >> 2);
            const uint4* po = reinterpret_cast<const uint4*>(g_o + cta * 512) + lane;
            uint2 ml[4];
            uint4 v[4];
            bar_sync(7, 64);
            delay(O_DELAY);
#pragma unroll
            for (int i = 0; i < 4; i++) ml[i] = ld_poll2(pml + 16 * i);
#pragma unroll
            for (int i = 0; i < 4; i++) v[i] = ld_poll4(po + 32 * i);
#pragma unroll 1
            for (int it = 0; it < SPIN_LIMIT; it++) {
                bool ok = true;
#pragma unroll
                for (int i = 0; i < 4; i++) {
                    if (!tagged(v[i], tag)) { v[i] = ld_poll4(po + 32 * i); ok = false; }
                    if (((ml[i].x ^ tag) | (ml[i].y ^ tag)) & TAGM) { ml[i] = ld_poll2(pml + 16 * i); ok = false; }
                }
                if (__all_sync(~0u, ok)) break;
            }
            float M = fmaxf(fmaxf(untag(ml[0].x), untag(ml[1].x)), fmaxf(untag(ml[2].x), untag(ml[3].x)));
            M = fmaxf(M, __shfl_xor_sync(~0u, M, 8));
            M = fmaxf(M, __shfl_xor_sync(~0u, M, 16));
            float a0 = 0.f, a1 = 0.f, a2 = 0.f, a3 = 0.f, L = 0.f;
#pragma unroll
            for (int i = 0; i < 4; i++) {
                const float w = __expf(untag(ml[i].x) - M);
                L += w * untag(ml[i].y);
                a0 += w * untag(v[i].x); a1 += w * untag(v[i].y);
                a2 += w * untag(v[i].z); a3 += w * untag(v[i].w);
            }
#pragma unroll
            for (int s = 8; s < 32; s <<= 1) {
                L += __shfl_xor_sync(~0u, L, s);
                a0 += __shfl_xor_sync(~0u, a0, s); a1 += __shfl_xor_sync(~0u, a1, s);
                a2 += __shfl_xor_sync(~0u, a2, s); a3 += __shfl_xor_sync(~0u, a3, s);
            }
            L = __fdividef(1.f, L);
            if (lane < 8) st_pair(sb + SM_O + rank * 64 + lane * 8, bars + 128, pack_bf(a0 * L, a1 * L), pack_bf(a2 * L, a3 * L));
        }
        return;
    }

    const int g = lane >> 2, t = lane & 3;
    const int lrow = (lane & 7) + ((lane >> 4) << 3);
    const int lch = (lane >> 3) & 1;
    {
        uint32_t ofs = (warp * 32 + g) * 8192 + cta * 64 + t * 16;
        uint32_t dst = sb + SM_W + (warp * 64 + g) * 64 + ((t ^ ((g >> 1) & 3)) << 4);
        asm volatile("" : "+r"(ofs), "+r"(dst));
        if ((ofs ^ dst) == 1u) return;
        const char* src = reinterpret_cast<const char*>(wq) + ofs;
#pragma unroll
        for (int i = 0; i < 8; i++)
            asm volatile("cp.async.cg.shared.global.L2::128B [%0], [%1], 16;" ::"r"(dst + i * 512), "l"(src + (size_t)((i >> 2) * 32 + (i & 3)) * 65536) : "memory");
        if ((warp & 3) == 3) {
            const uint32_t b = bars + 8 * (13 + (warp >> 2));
            if (lane == 0) mbar_init(b, 32);
            __syncwarp();
            asm volatile("cp.async.mbarrier.arrive.noinc.shared::cta.b64 [%0];" ::"r"(b) : "memory");
            bar_arrive(5, 96);
        }
    }
    cluster_arrive();
    uint32_t xn[8];
    uint32_t* const pqo = g_q + cta * 32 + lane;
    uint2* const pml = g_ml + cta * 4 + (g & 3);
    uint32_t* const po = g_o + ((h * 16 + (t & 1) * 8 + (warp >> 1)) * 16 + j) * 32 + (warp & 1) * 16 + (t >> 1) * 8 + g;
    unsigned long long* const pa = g_acc + (rank * 32 + (tid >> 3)) * 32 + (tid & 7);
    const int ocol = 256 * rank + 32 * warp + 8 * t + g;
    const uint32_t tag = __ldcg(&g_epoch);
    {
        const uint4 xa = __ldg(reinterpret_cast<const uint4*>(x) + lane);
        const uint4 xb = __ldg(reinterpret_cast<const uint4*>(x) + 32 + lane);
#pragma unroll
        for (int i = 0; i < 8; i++) xn[i] = __ldg(reinterpret_cast<const uint32_t*>(x) + (i >> 2) * 128 + warp * 16 + (i & 3) * 4 + t);
        if (pair == (tid >> 2)) atomicAdd(pa, to_fix(__bfloat162float(x[ocol])));
        const uint32_t xw[8] = {xa.x, xa.y, xa.z, xa.w, xb.x, xb.y, xb.z, xb.w};
        float s = 0.f;
#pragma unroll
        for (int i = 0; i < 8; i++) s += bflo(xw[i]) + bfhi(xw[i]);
#pragma unroll
        for (int o = 1; o < 32; o <<= 1) s += __shfl_xor_sync(~0u, s, o);
        const float mean = s * (1.f / D_MODEL);
        float q = 0.f;
#pragma unroll
        for (int i = 0; i < 8; i++) {
            const float a = bflo(xw[i]) - mean, b = bfhi(xw[i]) - mean;
            q += a * a + b * b;
        }
#pragma unroll
        for (int o = 1; o < 32; o <<= 1) q += __shfl_xor_sync(~0u, q, o);
        const float mb = bfr(mean);
        float sd;
        asm("sqrt.approx.f32 %0, %1;" : "=f"(sd) : "f"(bfr(bfr(q * (1.f / D_MODEL)) + 1e-5f)));
        const float rden = __fdividef(1.f, bfr(sd));
#pragma unroll
        for (int i = 0; i < 8; i++) xn[i] = pack_bf(bfr(bflo(xn[i]) - mb) * rden, bfr(bfhi(xn[i]) - mb) * rden);
    }
    asm volatile("cp.async.wait_all;" ::: "memory");
    __syncwarp();
    {
        float c0[4] = {0.f, 0.f, 0.f, 0.f}, c1[4] = {0.f, 0.f, 0.f, 0.f};
        const uint32_t base = sb + SM_W + (warp * 64 + lrow) * 64;
        const int sw = (lane >> 1) & 3;
#pragma unroll
        for (int s = 0; s < 4; s++) {
            uint32_t a[4], b[4];
            ldsm4t(a, base + s * 1024 + ((lch ^ sw) << 4));
            ldsm4t(b, base + s * 1024 + (((2 + lch) ^ sw) << 4));
            mma(c0, a[0], a[1], a[2], a[3], xn[2 * s], xn[2 * s + 1]);
            mma(c1, b[0], b[1], b[2], b[3], xn[2 * s], xn[2 * s + 1]);
        }
        reinterpret_cast<float*>(smem + SM_PART)[warp * 32 + 8 * t + g] = sel4(t, c0[0], c0[2], c1[0], c1[2]);
    }
    bar_arrive(2, 288);
    bar_sync(1, 288);
    if (warp == 0) {
        float s = 0.f;
#pragma unroll
        for (int w = 0; w < 8; w++) s += reinterpret_cast<const float*>(smem + SM_PART)[w * 32 + lane];
        st_pub1(pqo, __float_as_uint(bfr(s)) | tag);
    }
    if (tid < 128) {
        const uint4* pq = reinterpret_cast<const uint4*>(g_q + h * 512) + tid;
        uint4 v;
        delay(Q_DELAY);
#pragma unroll 1
        for (int it = 0; it < SPIN_LIMIT; it++) {
            v = ld_poll4(pq);
            if (tagged(v, tag)) break;
        }
        *reinterpret_cast<uint2*>(smem + SM_Q + warp * 272 + lane * 8) =
            make_uint2(__byte_perm(v.x, v.y, 0x7632), __byte_perm(v.z, v.w, 0x7632));
    }
    bar_sync(3, 256);
    const int head = g & 3;
    float sc[4];
    {
        uint32_t qa[4][4];
#pragma unroll
        for (int i = 0; i < 4; i++) ldsm4(qa[i], sb + SM_Q + (lane & 3) * 272 + (4 * i + (lane >> 3)) * 16);
        mbar_wait(bars + 8 * (warp >> 1));
        float c[4][4];
        const uint32_t kb = sb + SM_K + (warp >> 1) * 16384 + (32 * (warp & 1) + (lane & 7)) * 128;
#pragma unroll
        for (int n = 0; n < 4; n++) {
#pragma unroll
            for (int e = 0; e < 4; e++) c[n][e] = 0.f;
#pragma unroll
            for (int i = 0; i < 4; i++) {
                uint32_t b[4];
                ldsm4(b, kb + n * 1024 + (i >> 1) * 8192 + (((4 * (i & 1) + (lane >> 3)) ^ (lane & 7)) << 4));
                mma(c[n], qa[i][0], 0u, qa[i][1], 0u, b[0], b[1]);
                mma(c[n], qa[i][2], 0u, qa[i][3], 0u, b[2], b[3]);
            }
        }
        const bool up = g >= 4;
        const float scale = 0.08838834764831845f;
        sc[0] = bfr(bfr(up ? c[2][0] : c[0][0]) * scale);
        sc[1] = bfr(bfr(up ? c[2][1] : c[0][1]) * scale);
        sc[2] = bfr(bfr(up ? c[3][0] : c[1][0]) * scale);
        sc[3] = bfr(bfr(up ? c[3][1] : c[1][1]) * scale);
    }
    float mcta;
    {
        float m = fmaxf(fmaxf(sc[0], sc[1]), fmaxf(sc[2], sc[3]));
        m = fmaxf(m, __shfl_xor_sync(~0u, m, 1));
        m = fmaxf(m, __shfl_xor_sync(~0u, m, 2));
        m = fmaxf(m, __shfl_xor_sync(~0u, m, 16));
        if (t == 0 && g < 4) reinterpret_cast<float*>(smem + SM_MX)[g * 8 + warp] = m;
        bar_sync(3, 256);
        const float4 m0 = *reinterpret_cast<const float4*>(smem + SM_MX + head * 32);
        const float4 m1 = *reinterpret_cast<const float4*>(smem + SM_MX + head * 32 + 16);
        mcta = fmaxf(fmaxf(fmaxf(m0.x, m0.y), fmaxf(m0.z, m0.w)), fmaxf(fmaxf(m1.x, m1.y), fmaxf(m1.z, m1.w)));
        const float p0 = __expf(sc[0] - mcta), p1 = __expf(sc[1] - mcta), p2 = __expf(sc[2] - mcta), p3 = __expf(sc[3] - mcta);
        uint8_t* pp = smem + SM_P + head * 528 + (32 * warp + 16 * (g >> 2) + 2 * t) * 2;
        *reinterpret_cast<uint32_t*>(pp) = pack_bf(p0, p1);
        *reinterpret_cast<uint32_t*>(pp + 16) = pack_bf(p2, p3);
        float l = (p0 + p1) + (p2 + p3);
        l += __shfl_xor_sync(~0u, l, 1);
        l += __shfl_xor_sync(~0u, l, 2);
        l += __shfl_xor_sync(~0u, l, 16);
        if (t == 0 && g < 4) reinterpret_cast<float*>(smem + SM_SUM)[g * 8 + warp] = l;
        bar_sync(3, 256);
        if (warp == 0 && t == 0 && g < 4) {
            const float4 l0 = *reinterpret_cast<const float4*>(smem + SM_SUM + head * 32);
            const float4 l1 = *reinterpret_cast<const float4*>(smem + SM_SUM + head * 32 + 16);
            const float ls = ((l0.x + l0.y) + (l0.z + l0.w)) + ((l1.x + l1.y) + (l1.z + l1.w));
            st_pub2(pml, tagf(mcta, tag), tagf(ls, tag));
        }
    }
    {
        float c0[4] = {0.f, 0.f, 0.f, 0.f}, c1[4] = {0.f, 0.f, 0.f, 0.f};
        const uint32_t pb = sb + SM_P + (lane & 3) * 528 + (lane >> 3) * 16;
        const uint32_t vb = sb + SM_V + (warp >> 2) * 8192 + lrow * 128 + (((2 * (warp & 3) + lch) ^ (lane & 7)) << 4);
#pragma unroll
        for (int i = 0; i < 4; i++) {
            uint32_t p0[4], p1[4], a[4][4];
            ldsm4(p0, pb + i * 128);
            ldsm4(p1, pb + i * 128 + 64);
            mbar_wait(bars + 32 + 8 * i);
#pragma unroll
            for (int s = 0; s < 4; s++) ldsm4t(a[s], vb + i * 16384 + s * 2048);
            mma(c0, a[0][0], a[0][1], a[0][2], a[0][3], p0[0], p0[1]);
            mma(c1, a[1][0], a[1][1], a[1][2], a[1][3], p0[2], p0[3]);
            mma(c0, a[2][0], a[2][1], a[2][2], a[2][3], p1[0], p1[1]);
            mma(c1, a[3][0], a[3][1], a[3][2], a[3][3], p1[2], p1[3]);
        }
        const bool up = t >= 2;
        const float v0 = up ? c0[2] + c1[2] : c0[0] + c1[0];
        const float v1 = up ? c0[3] + c1[3] : c0[1] + c1[1];
        st_pub1(po, tagf(v0, tag));
        st_pub1(po + 4 * 512, tagf(v1, tag));
        if (warp == 0) bar_arrive(7, 64);
    }
    float y0[4] = {0.f, 0.f, 0.f, 0.f}, y1[4] = {0.f, 0.f, 0.f, 0.f};
    const uint32_t wofs = (warp >> 1) * 4096 + lrow * 128 + (((4 * (warp & 1) + lch) ^ (lane & 7)) << 4);
    if (has_ffn) {
        float c[4][4];
        const uint32_t base = sb + SM_G + (warp * 32 + lrow) * 64 + ((lch ^ ((lane >> 1) & 3)) << 4);
        const uint32_t x0 = rank ? xn[4] : xn[0], x1 = rank ? xn[5] : xn[1], x2 = rank ? xn[6] : xn[2], x3 = rank ? xn[7] : xn[3];
        cluster_wait();
#pragma unroll
        for (int m = 0; m < 4; m++) {
            uint32_t a[4], b[4];
            if (!(m & 1)) mbar_wait(bars + 64 + 4 * m);
            ldsm4t(a, (base ^ ((m & 1) << 5)) + (m >> 1) * 16384);
            ldsm4t(b, (base ^ ((m & 1) << 5)) + (m >> 1) * 16384 + 1024);
#pragma unroll
            for (int e = 0; e < 4; e++) c[m][e] = 0.f;
            mma(c[m], a[0], a[1], a[2], a[3], x0, x1);
            mma(c[m], b[0], b[1], b[2], b[3], x2, x3);
        }
        st_pair(sb + SM_PART2 + (rank * 8 + warp) * 256 + (8 * t + g) * 8, bars + 120,
                __float_as_uint(sel4(t, c[0][0], c[0][2], c[1][0], c[1][2])), __float_as_uint(sel4(t, c[2][0], c[2][2], c[3][0], c[3][2])));
        mbar_wait(bars + 120);
        float gs = 0.f, us = 0.f;
#pragma unroll
        for (int w = 0; w < 16; w++) {
            const float2 v = reinterpret_cast<const float2*>(smem + SM_PART2)[w * 32 + lane];
            gs += v.x;
            us += v.y;
        }
        gs = bfr(gs);
        const float hv = bfr(__fdividef(gs, 1.f + __expf(-gs))) * bfr(us);
        const uint32_t hp = pack_bf(hv, __shfl_down_sync(~0u, hv, 1));
        uint32_t hb[4];
#pragma unroll
        for (int i = 0; i < 4; i++) hb[i] = __shfl_sync(~0u, hp, 8 * i + 2 * t);
        mbar_wait(bars + 80);
#pragma unroll
        for (int s = 0; s < 2; s++) {
            uint32_t a[4], b[4];
            ldsm4t(a, sb + SM_D + s * 2048 + wofs);
            ldsm4t(b, sb + SM_D + s * 2048 + (wofs ^ 32));
            mma(y0, a[0], a[1], a[2], a[3], hb[2 * s], hb[2 * s + 1]);
            mma(y1, b[0], b[1], b[2], b[3], hb[2 * s], hb[2 * s + 1]);
        }
    }
    mbar_wait(bars + 128);
    {
        uint32_t ob[8];
#pragma unroll
        for (int i = 0; i < 8; i++) ob[i] = *reinterpret_cast<const uint32_t*>(smem + SM_O + i * 16 + t * 4);
        __nv_bfloat16* pout = out + ocol;
        asm volatile("" : "+l"(pout));
        float z0[4] = {0.f, 0.f, 0.f, 0.f}, z1[4] = {0.f, 0.f, 0.f, 0.f};
#pragma unroll
        for (int s = 0; s < 4; s++) {
            uint32_t a[4], b[4];
            if (!(s & 1)) mbar_wait(bars + 88 + 4 * s);
            ldsm4t(a, sb + SM_W + (s >> 1) * 16384 + (s & 1) * 2048 + wofs);
            ldsm4t(b, sb + SM_W + (s >> 1) * 16384 + (s & 1) * 2048 + (wofs ^ 32));
            mma((s & 1) ? z0 : y0, a[0], a[1], a[2], a[3], ob[2 * s], ob[2 * s + 1]);
            mma((s & 1) ? z1 : y1, b[0], b[1], b[2], b[3], ob[2 * s], ob[2 * s + 1]);
        }
        const unsigned long long f = to_fix(sel4(t, y0[0], y0[2], y1[0], y1[2]) + sel4(t, z0[0], z0[2], z1[0], z1[2]));
        const unsigned long long a = atomicAdd(pa, f) + (f - (NCTA / 2 + 1));
        if (((uint32_t)a & 255u) == 0) {
            asm volatile("st.global.u16 [%0], %1;" ::"l"(pout), "h"(__bfloat16_as_ushort(__float2bfloat16_rn(from_fix(a)))) : "memory");
            *pa = 0;
            if (ocol == 0) g_epoch = tag == TAGM ? 1u : tag + 1;
        }
    }
}

typedef CUresult (*EncodeFn)(CUtensorMap*, CUtensorMapDataType, cuuint32_t, void*, const cuuint64_t*, const cuuint64_t*,
                             const cuuint32_t*, const cuuint32_t*, CUtensorMapInterleave, CUtensorMapSwizzle,
                             CUtensorMapL2promotion, CUtensorMapFloatOOBfill);

void make_map(EncodeFn enc, CUtensorMap* m, void* p, uint64_t d0, uint64_t d1, uint64_t d2, uint64_t s1, uint64_t s2,
              uint32_t b0, uint32_t b1, uint32_t b2, CUtensorMapSwizzle sw) {
    cuuint64_t gd[3] = {d0, d1, d2};
    cuuint64_t gs[2] = {s1, s2};
    cuuint32_t bd[3] = {b0, b1, b2};
    cuuint32_t es[3] = {1, 1, 1};
    enc(m, CU_TENSOR_MAP_DATA_TYPE_BFLOAT16, 3, p, gd, gs, bd, es, CU_TENSOR_MAP_INTERLEAVE_NONE, sw,
        CU_TENSOR_MAP_L2_PROMOTION_L2_128B, CU_TENSOR_MAP_FLOAT_OOB_FILL_NONE);
}

}

extern "C" void kernel_launch(void* const* d_in, const int* in_sizes, int n_in, void* d_out, int out_size) {
    static EncodeFn enc = nullptr;
    if (!enc) {
        void* fn = nullptr;
        cudaDriverEntryPointQueryResult qr;
        cudaGetDriverEntryPoint("cuTensorMapEncodeTiled", &fn, cudaEnableDefault, &qr);
        enc = (EncodeFn)fn;
        cudaFuncSetAttribute(fused_decode_kernel, cudaFuncAttributeMaxDynamicSharedMemorySize, SM_TOTAL);
    }
    Maps m;
    make_map(enc, &m.m[0], d_in[1], 64, (uint64_t)HKV * SK, 2, DH * 2, 128, 64, 64, 2, CU_TENSOR_MAP_SWIZZLE_128B);
    make_map(enc, &m.m[1], d_in[2], 64, (uint64_t)HKV * SK, 2, DH * 2, 128, 64, 64, 2, CU_TENSOR_MAP_SWIZZLE_128B);
    make_map(enc, &m.m[2], d_in[6], FF, 256, 2, FF * 2, FF * 2 * 256, 32, 256, 1, CU_TENSOR_MAP_SWIZZLE_64B);
    make_map(enc, &m.m[3], d_in[7], FF, 256, 2, FF * 2, FF * 2 * 256, 32, 256, 1, CU_TENSOR_MAP_SWIZZLE_64B);
    make_map(enc, &m.m[4], d_in[8], 64, FF, 8, D_MODEL * 2, 128, 64, 32, 4, CU_TENSOR_MAP_SWIZZLE_128B);
    make_map(enc, &m.m[5], d_in[4], 64, 4096, 8, D_MODEL * 2, 128, 64, 32, 4, CU_TENSOR_MAP_SWIZZLE_128B);
    fused_decode_kernel<<<NCTA, NTHREADS, SM_TOTAL>>>((const __nv_bfloat16*)d_in[0], (const __nv_bfloat16*)d_in[3],
                                                      (__nv_bfloat16*)d_out, m);
}
```

```cpp
#include <cuda_runtime.h>
#include <cuda_bf16.h>
#include <cuda.h>
#include <stdint.h>

namespace {

constexpr int D_MODEL = 512, HKV = 8, SK = 65536, DH = 128, WIN = 4096, FF = 1792;
constexpr int NCTA = 128, NFFN = FF / 16, NTHREADS = 320;
constexpr unsigned long long DEP = 0xFFDE012345678ull;
constexpr int NFREE = 2;
#define TF 880
#define TA 672
#define TN 600
#define QD 2000
#define OD 1700
constexpr int T_FIRST = TF, T_ALL = TA, T_FFN = TN, T_NOFFN = 1500;
constexpr int Q_DELAY = QD, O_DELAY = OD;
constexpr uint32_t TAGM = 7u;
constexpr int SPIN_LIMIT = 1 << 20;

constexpr int SM_W = 0;
constexpr int SM_K = 32768;
constexpr int SM_V = SM_K + 65536;
constexpr int SM_G = SM_V + 65536;
constexpr int SM_U = SM_G + 16384;
constexpr int SM_D = SM_U + 16384;
constexpr int SM_BAR = SM_D + 16384;
constexpr int SM_PART = SM_BAR + 256;
constexpr int SM_Q = SM_PART + 1024;
constexpr int SM_P = SM_Q + 1088;
constexpr int SM_MX = SM_P + 2112;
constexpr int SM_SUM = SM_MX + 128;
constexpr int SM_O = SM_SUM + 128;
constexpr int SM_PART2 = SM_O + 128;
constexpr int SM_TOTAL = SM_PART2 + 4096;

struct __align__(64) Maps { CUtensorMap m[6]; };

__device__ uint32_t g_epoch = 1;
__device__ __align__(128) uint32_t g_q[NCTA * 32];
__device__ __align__(128) uint32_t g_o[NCTA * 16 * 32];
__device__ __align__(128) uint2 g_ml[HKV * 4 * 16];
__device__ __align__(128) unsigned long long g_acc[D_MODEL / 8 * 32];

__device__ __forceinline__ void mbar_init(uint32_t a, int n) { asm volatile("mbarrier.init.shared::cta.b64 [%0], %1;" ::"r"(a), "r"(n) : "memory"); }
__device__ __forceinline__ void mbar_expect(uint32_t a, int bytes) {
    asm volatile("mbarrier.arrive.expect_tx.shared::cta.b64 _, [%0], %1;" ::"r"(a), "r"(bytes) : "memory");
}
__device__ __forceinline__ void mbar_wait(uint32_t a) {
    uint32_t ok;
    int it = 0;
#pragma unroll 1
    do {
        asm volatile("{\n.reg .pred p;\nmbarrier.try_wait.parity.shared::cta.b64 p, [%1], 0;\nselp.u32 %0, 1, 0, p;\n}"
                     : "=r"(ok) : "r"(a) : "memory");
    } while (!ok && ++it < 4096);
}
__device__ __forceinline__ void tma3d(uint32_t dst, const CUtensorMap* m, int c0, int c1, int c2, uint32_t bar) {
    asm volatile("cp.async.bulk.tensor.3d.shared::cluster.global.mbarrier::complete_tx::bytes [%0], [%1, {%3, %4, %5}], [%2];"
                 ::"r"(dst), "l"(m), "r"(bar), "r"(c0), "r"(c1), "r"(c2) : "memory");
}
__device__ __forceinline__ void st_pair(uint32_t dst, uint32_t bar, uint32_t a, uint32_t b) {
#pragma unroll
    for (int r = 0; r < 2; r++) {
        uint32_t d, m;
        asm("mapa.shared::cluster.u32 %0, %1, %2;" : "=r"(d) : "r"(dst), "r"(r));
        asm("mapa.shared::cluster.u32 %0, %1, %2;" : "=r"(m) : "r"(bar), "r"(r));
        asm volatile("st.async.weak.shared::cluster.mbarrier::complete_tx::bytes.v2.b32 [%0], {%1,%2}, [%3];"
                     ::"r"(d), "r"(a), "r"(b), "r"(m) : "memory");
    }
}
__device__ __forceinline__ void cluster_arrive() { asm volatile("barrier.cluster.arrive.relaxed.aligned;" ::: "memory"); }
__device__ __forceinline__ void cluster_wait() { asm volatile("barrier.cluster.wait.acquire.aligned;" ::: "memory"); }
__device__ __forceinline__ void bar_sync(int id, int n) { asm volatile("bar.sync %0, %1;" ::"r"(id), "r"(n) : "memory"); }
__device__ __forceinline__ void bar_arrive(int id, int n) { asm volatile("bar.arrive %0, %1;" ::"r"(id), "r"(n) : "memory"); }
__device__ __forceinline__ void ldsm4(uint32_t (&r)[4], uint32_t a) {
    asm volatile("ldmatrix.sync.aligned.m8n8.x4.shared.b16 {%0,%1,%2,%3}, [%4];"
                 : "=r"(r[0]), "=r"(r[1]), "=r"(r[2]), "=r"(r[3]) : "r"(a) : "memory");
}
__device__ __forceinline__ void ldsm4t(uint32_t (&r)[4], uint32_t a) {
    asm volatile("ldmatrix.sync.aligned.m8n8.x4.trans.shared.b16 {%0,%1,%2,%3}, [%4];"
                 : "=r"(r[0]), "=r"(r[1]), "=r"(r[2]), "=r"(r[3]) : "r"(a) : "memory");
}
__device__ __forceinline__ void mma(float (&c)[4], uint32_t a0, uint32_t a1, uint32_t a2, uint32_t a3, uint32_t b0, uint32_t b1) {
    asm volatile("mma.sync.aligned.m16n8k16.row.col.f32.bf16.bf16.f32 {%0,%1,%2,%3}, {%4,%5,%6,%7}, {%8,%9}, {%0,%1,%2,%3};"
                 : "+f"(c[0]), "+f"(c[1]), "+f"(c[2]), "+f"(c[3])
                 : "r"(a0), "r"(a1), "r"(a2), "r"(a3), "r"(b0), "r"(b1));
}
__device__ __forceinline__ uint4 ld_poll4(const void* p) {
    uint4 v;
    asm volatile("ld.relaxed.gpu.global.v4.u32 {%0,%1,%2,%3}, [%4];" : "=r"(v.x), "=r"(v.y), "=r"(v.z), "=r"(v.w) : "l"(p) : "memory");
    return v;
}
__device__ __forceinline__ uint2 ld_poll2(const void* p) {
    uint2 v;
    asm volatile("ld.relaxed.gpu.global.v2.u32 {%0,%1}, [%2];" : "=r"(v.x), "=r"(v.y) : "l"(p) : "memory");
    return v;
}
__device__ __forceinline__ void st_pub1(void* p, uint32_t v) { asm volatile("st.relaxed.gpu.global.u32 [%0], %1;" ::"l"(p), "r"(v) : "memory"); }
__device__ __forceinline__ void st_pub2(void* p, uint32_t a, uint32_t b) {
    asm volatile("st.relaxed.gpu.global.v2.u32 [%0], {%1,%2};" ::"l"(p), "r"(a), "r"(b) : "memory");
}
__device__ __forceinline__ bool tagged(uint4 v, uint32_t tag) { return (((v.x ^ tag) | (v.y ^ tag) | (v.z ^ tag) | (v.w ^ tag)) & TAGM) == 0; }
__device__ __forceinline__ void delay(uint32_t cycles) {
    uint32_t t0, t1;
    asm volatile("mov.u32 %0, %%clock;" : "=r"(t0));
    do { asm volatile("mov.u32 %0, %%clock;" : "=r"(t1)); } while (t1 - t0 < cycles);
}
__device__ __forceinline__ uint32_t now_ns() { uint32_t t; asm volatile("mov.u32 %0, %%globaltimer_lo;" : "=r"(t)); return t; }
__device__ __forceinline__ unsigned long long to_fix(float v) { return ((unsigned long long)__float2ll_rn(v * 68719476736.f) & ~255ull) | 1ull; }
__device__ __forceinline__ float from_fix(unsigned long long a) { return __ll2float_rn((long long)a) * (1.f / 68719476736.f); }
__device__ __forceinline__ uint32_t tagf(float f, uint32_t tag) { return (__float_as_uint(f) & ~TAGM) | tag; }
__device__ __forceinline__ float untag(uint32_t u) { return __uint_as_float(u & ~TAGM); }
__device__ __forceinline__ float bfr(float f) { return __bfloat162float(__float2bfloat16_rn(f)); }
__device__ __forceinline__ float bflo(uint32_t u) { return __uint_as_float(u << 16); }
__device__ __forceinline__ float bfhi(uint32_t u) { return __uint_as_float(u & 0xffff0000u); }
__device__ __forceinline__ uint32_t pack_bf(float lo, float hi) {
    __nv_bfloat162 v = __floats2bfloat162_rn(lo, hi);
    return *reinterpret_cast<uint32_t*>(&v);
}
__device__ __forceinline__ float sel4(int t, float a, float b, float c, float d) { return (t & 2) ? ((t & 1) ? d : c) : ((t & 1) ? b : a); }

__global__ void __cluster_dims__(2, 1, 1) __launch_bounds__(NTHREADS, 1)
fused_decode_kernel(const __nv_bfloat16* __restrict__ x, const __nv_bfloat16* __restrict__ wq,
                    __nv_bfloat16* __restrict__ out, const __grid_constant__ Maps maps) {
    const uint32_t t_start = now_ns();
    extern __shared__ __align__(1024) uint8_t smem[];
    const uint32_t sb = (uint32_t)__cvta_generic_to_shared(smem);
    const int tid = threadIdx.x, lane = tid & 31;
    const int warp = tid >> 5;
    const int cta = blockIdx.x, h = cta >> 4, j = cta & 15, pair = cta >> 1, rank = cta & 1;
    const uint32_t bars = sb + SM_BAR;
    const bool has_ffn = cta < NFFN;

    if (warp == 8) {
        uint32_t due = t_start + T_FIRST + cta * T_ALL / NCTA;
        const int u = (!has_ffn && lane >= 8) ? lane + 3 : lane;
        if (lane == 0) {
#pragma unroll
            for (int i = 0; i < 17; i++)
                if (i < 13 || i > 14) mbar_init(bars + 8 * i, 1);
            mbar_expect(bars + 120, 4096);
            mbar_expect(bars + 128, 128);
        }
        asm volatile("fence.proxy.async.shared::cta;" ::: "memory");
        __syncwarp();
        const int mi = u < 8 ? (u >> 2) : min(u - 6, 5);
        const int c0 = (u == 8 || u == 9) ? pair * 32 : 0;
        const int c1 = u < 8 ? h * SK + (SK - WIN) + (u & 3) * 1024 + j * 64 : (u < 10 ? 0 : (u == 10 ? pair * 32 : pair * 64 + (u - 11) * 32));
        const int c2 = u < 8 ? 0 : (u < 10 ? rank : 4 * rank);
        const uint32_t dst = sb + (u < 11 ? SM_K + u * 16384 : SM_W + (u - 11) * 16384);
        const int n = has_ffn ? 13 : 10;
        asm volatile("fence.mbarrier_init.release.cluster;" ::: "memory");
        cluster_arrive();
        bar_arrive(1, 288);
#pragma unroll 1
        for (int i = 0; i < n; i++) {
            if (i == NFREE) bar_sync(5, 96);
            if (i == n - 2) {
                bar_sync(2, 288);
                asm volatile("fence.proxy.async.shared::cta;" ::: "memory");
            }
            if (i >= NFREE) mbar_wait(bars + 8 * (int)((DEP >> (48 - 4 * i)) & 15));
            for (int it = 0; it < 1024 && (int)(now_ns() - due) < 0; it++) {}
            due += (i < 7 || (i == 7 && has_ffn)) ? T_ALL : (has_ffn ? T_FFN : T_NOFFN);
            if (lane == i) {
                mbar_expect(bars + 8 * u, 16384);
                tma3d(dst, &maps.m[mi], c0, c1, c2, bars + 8 * u);
            }
            __syncwarp();
        }
        return;
    }
    if (warp == 9) {
        const uint32_t tag = __ldcg(&g_epoch);
        cluster_arrive();
        cluster_wait();
        {
            const uint2* pml = g_ml + (h * 16 + (lane >> 3)) * 4 + (j >> 2);
            const uint4* po = reinterpret_cast<const uint4*>(g_o + cta * 512) + lane;
            uint2 ml[4];
            uint4 v[4];
            bar_sync(7, 64);
            delay(O_DELAY);
#pragma unroll
            for (int i = 0; i < 4; i++) ml[i] = ld_poll2(pml + 16 * i);
#pragma unroll
            for (int i = 0; i < 4; i++) v[i] = ld_poll4(po + 32 * i);
#pragma unroll 1
            for (int it = 0; it < SPIN_LIMIT; it++) {
                bool ok = true;
#pragma unroll
                for (int i = 0; i < 4; i++) {
                    if (!tagged(v[i], tag)) { v[i] = ld_poll4(po + 32 * i); ok = false; }
                    if (((ml[i].x ^ tag) | (ml[i].y ^ tag)) & TAGM) { ml[i] = ld_poll2(pml + 16 * i); ok = false; }
                }
                if (__all_sync(~0u, ok)) break;
            }
            float M = fmaxf(fmaxf(untag(ml[0].x), untag(ml[1].x)), fmaxf(untag(ml[2].x), untag(ml[3].x)));
            M = fmaxf(M, __shfl_xor_sync(~0u, M, 8));
            M = fmaxf(M, __shfl_xor_sync(~0u, M, 16));
            float a0 = 0.f, a1 = 0.f, a2 = 0.f, a3 = 0.f, L = 0.f;
#pragma unroll
            for (int i = 0; i < 4; i++) {
                const float w = __expf(untag(ml[i].x) - M);
                L += w * untag(ml[i].y);
                a0 += w * untag(v[i].x); a1 += w * untag(v[i].y);
                a2 += w * untag(v[i].z); a3 += w * untag(v[i].w);
            }
#pragma unroll
            for (int s = 8; s < 32; s <<= 1) {
                L += __shfl_xor_sync(~0u, L, s);
                a0 += __shfl_xor_sync(~0u, a0, s); a1 += __shfl_xor_sync(~0u, a1, s);
                a2 += __shfl_xor_sync(~0u, a2, s); a3 += __shfl_xor_sync(~0u, a3, s);
            }
            L = __fdividef(1.f, L);
            if (lane < 8) st_pair(sb + SM_O + rank * 64 + lane * 8, bars + 128, pack_bf(a0 * L, a1 * L), pack_bf(a2 * L, a3 * L));
        }
        return;
    }

    const int g = lane >> 2, t = lane & 3;
    const int lrow = (lane & 7) + ((lane >> 4) << 3);
    const int lch = (lane >> 3) & 1;
    {
        uint32_t ofs = (warp * 32 + g) * 8192 + cta * 64 + t * 16;
        uint32_t dst = sb + SM_W + (warp * 64 + g) * 64 + ((t ^ ((g >> 1) & 3)) << 4);
        asm volatile("" : "+r"(ofs), "+r"(dst));
        if ((ofs ^ dst) == 1u) return;
        const char* src = reinterpret_cast<const char*>(wq) + ofs;
#pragma unroll
        for (int i = 0; i < 8; i++)
            asm volatile("cp.async.cg.shared.global.L2::128B [%0], [%1], 16;" ::"r"(dst + i * 512), "l"(src + (size_t)((i >> 2) * 32 + (i & 3)) * 65536) : "memory");
        if ((warp & 3) == 3) {
            const uint32_t b = bars + 8 * (13 + (warp >> 2));
            if (lane == 0) mbar_init(b, 32);
            __syncwarp();
            asm volatile("cp.async.mbarrier.arrive.noinc.shared::cta.b64 [%0];" ::"r"(b) : "memory");
            bar_arrive(5, 96);
        }
    }
    cluster_arrive();
    uint32_t xn[8];
    uint32_t* const pqo = g_q + cta * 32 + lane;
    uint2* const pml = g_ml + cta * 4 + (g & 3);
    uint32_t* const po = g_o + ((h * 16 + (t & 1) * 8 + (warp >> 1)) * 16 + j) * 32 + (warp & 1) * 16 + (t >> 1) * 8 + g;
    unsigned long long* const pa = g_acc + (rank * 32 + (tid >> 3)) * 32 + (tid & 7);
    const int ocol = 256 * rank + 32 * warp + 8 * t + g;
    const uint32_t tag = __ldcg(&g_epoch);
    {
        const uint4 xa = __ldg(reinterpret_cast<const uint4*>(x) + lane);
        const uint4 xb = __ldg(reinterpret_cast<const uint4*>(x) + 32 + lane);
#pragma unroll
        for (int i = 0; i < 8; i++) xn[i] = __ldg(reinterpret_cast<const uint32_t*>(x) + (i >> 2) * 128 + warp * 16 + (i & 3) * 4 + t);
        if (pair == (tid >> 2)) atomicAdd(pa, to_fix(__bfloat162float(x[ocol])));
        const uint32_t xw[8] = {xa.x, xa.y, xa.z, xa.w, xb.x, xb.y, xb.z, xb.w};
        float s = 0.f;
#pragma unroll
        for (int i = 0; i < 8; i++) s += bflo(xw[i]) + bfhi(xw[i]);
#pragma unroll
        for (int o = 1; o < 32; o <<= 1) s += __shfl_xor_sync(~0u, s, o);
        const float mean = s * (1.f / D_MODEL);
        float q = 0.f;
#pragma unroll
        for (int i = 0; i < 8; i++) {
            const float a = bflo(xw[i]) - mean, b = bfhi(xw[i]) - mean;
            q += a * a + b * b;
        }
#pragma unroll
        for (int o = 1; o < 32; o <<= 1) q += __shfl_xor_sync(~0u, q, o);
        const float mb = bfr(mean);
        float sd;
        asm("sqrt.approx.f32 %0, %1;" : "=f"(sd) : "f"(bfr(bfr(q * (1.f / D_MODEL)) + 1e-5f)));
        const float rden = __fdividef(1.f, bfr(sd));
#pragma unroll
        for (int i = 0; i < 8; i++) xn[i] = pack_bf(bfr(bflo(xn[i]) - mb) * rden, bfr(bfhi(xn[i]) - mb) * rden);
    }
    asm volatile("cp.async.wait_all;" ::: "memory");
    __syncwarp();
    {
        float c0[4] = {0.f, 0.f, 0.f, 0.f}, c1[4] = {0.f, 0.f, 0.f, 0.f};
        const uint32_t base = sb + SM_W + (warp * 64 + lrow) * 64;
        const int sw = (lane >> 1) & 3;
#pragma unroll
        for (int s = 0; s < 4; s++) {
            uint32_t a[4], b[4];
            ldsm4t(a, base + s * 1024 + ((lch ^ sw) << 4));
            ldsm4t(b, base + s * 1024 + (((2 + lch) ^ sw) << 4));
            mma(c0, a[0], a[1], a[2], a[3], xn[2 * s], xn[2 * s + 1]);
            mma(c1, b[0], b[1], b[2], b[3], xn[2 * s], xn[2 * s + 1]);
        }
        reinterpret_cast<float*>(smem + SM_PART)[warp * 32 + 8 * t + g] = sel4(t, c0[0], c0[2], c1[0], c1[2]);
    }
    bar_arrive(2, 288);
    bar_sync(1, 288);
    if (warp == 0) {
        float s = 0.f;
#pragma unroll
        for (int w = 0; w < 8; w++) s += reinterpret_cast<const float*>(smem + SM_PART)[w * 32 + lane];
        st_pub1(pqo, __float_as_uint(bfr(s)) | tag);
    }
    if (tid < 128) {
        const uint4* pq = reinterpret_cast<const uint4*>(g_q + h * 512) + tid;
        uint4 v;
        delay(Q_DELAY);
#pragma unroll 1
        for (int it = 0; it < SPIN_LIMIT; it++) {
            v = ld_poll4(pq);
            if (tagged(v, tag)) break;
        }
        *reinterpret_cast<uint2*>(smem + SM_Q + warp * 272 + lane * 8) =
            make_uint2(__byte_perm(v.x, v.y, 0x7632), __byte_perm(v.z, v.w, 0x7632));
    }
    bar_sync(3, 256);
    const int head = g & 3;
    float sc[4];
    {
        uint32_t qa[4][4];
#pragma unroll
        for (int i = 0; i < 4; i++) ldsm4(qa[i], sb + SM_Q + (lane & 3) * 272 + (4 * i + (lane >> 3)) * 16);
        mbar_wait(bars + 8 * (warp >> 1));
        float c[4][4];
        const uint32_t kb = sb + SM_K + (warp >> 1) * 16384 + (32 * (warp & 1) + (lane & 7)) * 128;
#pragma unroll
        for (int n = 0; n < 4; n++) {
#pragma unroll
            for (int e = 0; e < 4; e++) c[n][e] = 0.f;
#pragma unroll
            for (int i = 0; i < 4; i++) {
                uint32_t b[4];
                ldsm4(b, kb + n * 1024 + (i >> 1) * 8192 + (((4 * (i & 1) + (lane >> 3)) ^ (lane & 7)) << 4));
                mma(c[n], qa[i][0], 0u, qa[i][1], 0u, b[0], b[1]);
                mma(c[n], qa[i][2], 0u, qa[i][3], 0u, b[2], b[3]);
            }
        }
        const bool up = g >= 4;
        const float scale = 0.08838834764831845f;
        sc[0] = bfr(bfr(up ? c[2][0] : c[0][0]) * scale);
        sc[1] = bfr(bfr(up ? c[2][1] : c[0][1]) * scale);
        sc[2] = bfr(bfr(up ? c[3][0] : c[1][0]) * scale);
        sc[3] = bfr(bfr(up ? c[3][1] : c[1][1]) * scale);
    }
    float mcta;
    {
        float m = fmaxf(fmaxf(sc[0], sc[1]), fmaxf(sc[2], sc[3]));
        m = fmaxf(m, __shfl_xor_sync(~0u, m, 1));
        m = fmaxf(m, __shfl_xor_sync(~0u, m, 2));
        m = fmaxf(m, __shfl_xor_sync(~0u, m, 16));
        if (t == 0 && g < 4) reinterpret_cast<float*>(smem + SM_MX)[g * 8 + warp] = m;
        bar_sync(3, 256);
        const float4 m0 = *reinterpret_cast<const float4*>(smem + SM_MX + head * 32);
        const float4 m1 = *reinterpret_cast<const float4*>(smem + SM_MX + head * 32 + 16);
        mcta = fmaxf(fmaxf(fmaxf(m0.x, m0.y), fmaxf(m0.z, m0.w)), fmaxf(fmaxf(m1.x, m1.y), fmaxf(m1.z, m1.w)));
        const float p0 = __expf(sc[0] - mcta), p1 = __expf(sc[1] - mcta), p2 = __expf(sc[2] - mcta), p3 = __expf(sc[3] - mcta);
        uint8_t* pp = smem + SM_P + head * 528 + (32 * warp + 16 * (g >> 2) + 2 * t) * 2;
        *reinterpret_cast<uint32_t*>(pp) = pack_bf(p0, p1);
        *reinterpret_cast<uint32_t*>(pp + 16) = pack_bf(p2, p3);
        float l = (p0 + p1) + (p2 + p3);
        l += __shfl_xor_sync(~0u, l, 1);
        l += __shfl_xor_sync(~0u, l, 2);
        l += __shfl_xor_sync(~0u, l, 16);
        if (t == 0 && g < 4) reinterpret_cast<float*>(smem + SM_SUM)[g * 8 + warp] = l;
        bar_sync(3, 256);
        if (warp == 0 && t == 0 && g < 4) {
            const float4 l0 = *reinterpret_cast<const float4*>(smem + SM_SUM + head * 32);
            const float4 l1 = *reinterpret_cast<const float4*>(smem + SM_SUM + head * 32 + 16);
            const float ls = ((l0.x + l0.y) + (l0.z + l0.w)) + ((l1.x + l1.y) + (l1.z + l1.w));
            st_pub2(pml, tagf(mcta, tag), tagf(ls, tag));
        }
    }
    {
        float c0[4] = {0.f, 0.f, 0.f, 0.f}, c1[4] = {0.f, 0.f, 0.f, 0.f};
        const uint32_t pb = sb + SM_P + (lane & 3) * 528 + (lane >> 3) * 16;
        const uint32_t vb = sb + SM_V + (warp >> 2) * 8192 + lrow * 128 + (((2 * (warp & 3) + lch) ^ (lane & 7)) << 4);
#pragma unroll
        for (int i = 0; i < 4; i++) {
            uint32_t p0[4], p1[4], a[4][4];
            ldsm4(p0, pb + i * 128);
            ldsm4(p1, pb + i * 128 + 64);
            mbar_wait(bars + 32 + 8 * i);
#pragma unroll
            for (int s = 0; s < 4; s++) ldsm4t(a[s], vb + i * 16384 + s * 2048);
            mma(c0, a[0][0], a[0][1], a[0][2], a[0][3], p0[0], p0[1]);
            mma(c1, a[1][0], a[1][1], a[1][2], a[1][3], p0[2], p0[3]);
            mma(c0, a[2][0], a[2][1], a[2][2], a[2][3], p1[0], p1[1]);
            mma(c1, a[3][0], a[3][1], a[3][2], a[3][3], p1[2], p1[3]);
        }
        const bool up = t >= 2;
        const float v0 = up ? c0[2] + c1[2] : c0[0] + c1[0];
        const float v1 = up ? c0[3] + c1[3] : c0[1] + c1[1];
        st_pub1(po, tagf(v0, tag));
        st_pub1(po + 4 * 512, tagf(v1, tag));
        if (warp == 0) bar_arrive(7, 64);
    }
    float y0[4] = {0.f, 0.f, 0.f, 0.f}, y1[4] = {0.f, 0.f, 0.f, 0.f};
    const uint32_t wofs = (warp >> 1) * 4096 + lrow * 128 + (((4 * (warp & 1) + lch) ^ (lane & 7)) << 4);
    if (has_ffn) {
        float c[4][4];
        const uint32_t base = sb + SM_G + (warp * 32 + lrow) * 64 + ((lch ^ ((lane >> 1) & 3)) << 4);
        const uint32_t x0 = rank ? xn[4] : xn[0], x1 = rank ? xn[5] : xn[1], x2 = rank ? xn[6] : xn[2], x3 = rank ? xn[7] : xn[3];
        cluster_wait();
#pragma unroll
        for (int m = 0; m < 4; m++) {
            uint32_t a[4], b[4];
            if (!(m & 1)) mbar_wait(bars + 64 + 4 * m);
            ldsm4t(a, (base ^ ((m & 1) << 5)) + (m >> 1) * 16384);
            ldsm4t(b, (base ^ ((m & 1) << 5)) + (m >> 1) * 16384 + 1024);
#pragma unroll
            for (int e = 0; e < 4; e++) c[m][e] = 0.f;
            mma(c[m], a[0], a[1], a[2], a[3], x0, x1);
            mma(c[m], b[0], b[1], b[2], b[3], x2, x3);
        }
        st_pair(sb + SM_PART2 + (rank * 8 + warp) * 256 + (8 * t + g) * 8, bars + 120,
                __float_as_uint(sel4(t, c[0][0], c[0][2], c[1][0], c[1][2])), __float_as_uint(sel4(t, c[2][0], c[2][2], c[3][0], c[3][2])));
        mbar_wait(bars + 120);
        float gs = 0.f, us = 0.f;
#pragma unroll
        for (int w = 0; w < 16; w++) {
            const float2 v = reinterpret_cast<const float2*>(smem + SM_PART2)[w * 32 + lane];
            gs += v.x;
            us += v.y;
        }
        gs = bfr(gs);
        const float hv = bfr(__fdividef(gs, 1.f + __expf(-gs))) * bfr(us);
        const uint32_t hp = pack_bf(hv, __shfl_down_sync(~0u, hv, 1));
        uint32_t hb[4];
#pragma unroll
        for (int i = 0; i < 4; i++) hb[i] = __shfl_sync(~0u, hp, 8 * i + 2 * t);
        mbar_wait(bars + 80);
#pragma unroll
        for (int s = 0; s < 2; s++) {
            uint32_t a[4], b[4];
            ldsm4t(a, sb + SM_D + s * 2048 + wofs);
            ldsm4t(b, sb + SM_D + s * 2048 + (wofs ^ 32));
            mma(y0, a[0], a[1], a[2], a[3], hb[2 * s], hb[2 * s + 1]);
            mma(y1, b[0], b[1], b[2], b[3], hb[2 * s], hb[2 * s + 1]);
        }
    }
    mbar_wait(bars + 128);
    {
        uint32_t ob[8];
#pragma unroll
        for (int i = 0; i < 8; i++) ob[i] = *reinterpret_cast<const uint32_t*>(smem + SM_O + i * 16 + t * 4);
        __nv_bfloat16* pout = out + ocol;
        asm volatile("" : "+l"(pout));
        float z0[4] = {0.f, 0.f, 0.f, 0.f}, z1[4] = {0.f, 0.f, 0.f, 0.f};
#pragma unroll
        for (int s = 0; s < 4; s++) {
            uint32_t a[4], b[4];
            if (!(s & 1)) mbar_wait(bars + 88 + 4 * s);
            ldsm4t(a, sb + SM_W + (s >> 1) * 16384 + (s & 1) * 2048 + wofs);
            ldsm4t(b, sb + SM_W + (s >> 1) * 16384 + (s & 1) * 2048 + (wofs ^ 32));
            mma((s & 1) ? z0 : y0, a[0], a[1], a[2], a[3], ob[2 * s], ob[2 * s + 1]);
            mma((s & 1) ? z1 : y1, b[0], b[1], b[2], b[3], ob[2 * s], ob[2 * s + 1]);
        }
        const unsigned long long f = to_fix(sel4(t, y0[0], y0[2], y1[0], y1[2]) + sel4(t, z0[0], z0[2], z1[0], z1[2]));
        const unsigned long long a = atomicAdd(pa, f) + (f - (NCTA / 2 + 1));
        if (((uint32_t)a & 255u) == 0) {
            asm volatile("st.global.u16 [%0], %1;" ::"l"(pout), "h"(__bfloat16_as_ushort(__float2bfloat16_rn(from_fix(a)))) : "memory");
            *pa = 0;
            if (ocol == 0) g_epoch = tag == TAGM ? 1u : tag + 1;
        }
    }
}

typedef CUresult (*EncodeFn)(CUtensorMap*, CUtensorMapDataType, cuuint32_t, void*, const cuuint64_t*, const cuuint64_t*,
                             const cuuint32_t*, const cuuint32_t*, CUtensorMapInterleave, CUtensorMapSwizzle,
                             CUtensorMapL2promotion, CUtensorMapFloatOOBfill);

void make_map(EncodeFn enc, CUtensorMap* m, void* p, uint64_t d0, uint64_t d1, uint64_t d2, uint64_t s1, uint64_t s2,
              uint32_t b0, uint32_t b1, uint32_t b2, CUtensorMapSwizzle sw) {
    cuuint64_t gd[3] = {d0, d1, d2};
    cuuint64_t gs[2] = {s1, s2};
    cuuint32_t bd[3] = {b0, b1, b2};
    cuuint32_t es[3] = {1, 1, 1};
    enc(m, CU_TENSOR_MAP_DATA_TYPE_BFLOAT16, 3, p, gd, gs, bd, es, CU_TENSOR_MAP_INTERLEAVE_NONE, sw,
        CU_TENSOR_MAP_L2_PROMOTION_L2_128B, CU_TENSOR_MAP_FLOAT_OOB_FILL_NONE);
}

}

extern "C" void kernel_launch(void* const* d_in, const int* in_sizes, int n_in, void* d_out, int out_size) {
    static EncodeFn enc = nullptr;
    if (!enc) {
        void* fn = nullptr;
        cudaDriverEntryPointQueryResult qr;
        cudaGetDriverEntryPoint("cuTensorMapEncodeTiled", &fn, cudaEnableDefault, &qr);
        enc = (EncodeFn)fn;
        cudaFuncSetAttribute(fused_decode_kernel, cudaFuncAttributeMaxDynamicSharedMemorySize, SM_TOTAL);
    }
    Maps m;
    make_map(enc, &m.m[0], d_in[1], 64, (uint64_t)HKV * SK, 2, DH * 2, 128, 64, 64, 2, CU_TENSOR_MAP_SWIZZLE_128B);
    make_map(enc, &m.m[1], d_in[2], 64, (uint64_t)HKV * SK, 2, DH * 2, 128, 64, 64, 2, CU_TENSOR_MAP_SWIZZLE_128B);
    make_map(enc, &m.m[2], d_in[6], FF, 256, 2, FF * 2, FF * 2 * 256, 32, 256, 1, CU_TENSOR_MAP_SWIZZLE_64B);
    make_map(enc, &m.m[3], d_in[7], FF, 256, 2, FF * 2, FF * 2 * 256, 32, 256, 1, CU_TENSOR_MAP_SWIZZLE_64B);
    make_map(enc, &m.m[4], d_in[8], 64, FF, 8, D_MODEL * 2, 128, 64, 32, 4, CU_TENSOR_MAP_SWIZZLE_128B);
    make_map(enc, &m.m[5], d_in[4], 64, 4096, 8, D_MODEL * 2, 128, 64, 32, 4, CU_TENSOR_MAP_SWIZZLE_128B);
    fused_decode_kernel<<<NCTA, NTHREADS, SM_TOTAL>>>((const __nv_bfloat16*)d_in[0], (const __nv_bfloat16*)d_in[3],
                                                      (__nv_bfloat16*)d_out, m);
}
```

```cpp
#include <cuda_runtime.h>
#include <cuda_bf16.h>
#include <cuda.h>
#include <stdint.h>

namespace {

constexpr int D_MODEL = 512, HKV = 8, SK = 65536, DH = 128, WIN = 4096, FF = 1792;
constexpr int NCTA = 128, NFFN = FF / 16, NTHREADS = 320;
constexpr unsigned long long DEP = 0xFFDE012345678ull;
constexpr int NFREE = 2;
#define TF 880
#define TA 672
#define TN 600
#define QD 2000
#define OD 1700
constexpr int T_FIRST = TF, T_ALL = TA, T_FFN = TN, T_NOFFN = 1500;
constexpr int Q_DELAY = QD, O_DELAY = OD;
constexpr uint32_t TAGM = 7u;
constexpr int SPIN_LIMIT = 1 << 20;

constexpr int SM_W = 0;
constexpr int SM_K = 32768;
constexpr int SM_V = SM_K + 65536;
constexpr int SM_G = SM_V + 65536;
constexpr int SM_U = SM_G + 16384;
constexpr int SM_D = SM_U + 16384;
constexpr int SM_BAR = SM_D + 16384;
constexpr int SM_TAG = SM_BAR + 192;
constexpr int SM_PART = SM_BAR + 256;
constexpr int SM_Q = SM_PART + 1024;
constexpr int SM_P = SM_Q + 1088;
constexpr int SM_MX = SM_P + 2112;
constexpr int SM_SUM = SM_MX + 128;
constexpr int SM_O = SM_SUM + 128;
constexpr int SM_PART2 = SM_O + 128;
constexpr int SM_TOTAL = SM_PART2 + 4096;

struct __align__(64) Maps { CUtensorMap m[6]; };

__device__ uint32_t g_epoch = 1;
__device__ __align__(128) uint32_t g_q[NCTA * 32];
__device__ __align__(128) uint32_t g_o[NCTA * 16 * 32];
__device__ __align__(128) uint2 g_ml[HKV * 4 * 16];
__device__ __align__(128) unsigned long long g_acc[D_MODEL / 8 * 32];

__device__ __forceinline__ void mbar_init(uint32_t a, int n) { asm volatile("mbarrier.init.shared::cta.b64 [%0], %1;" ::"r"(a), "r"(n) : "memory"); }
__device__ __forceinline__ void mbar_expect(uint32_t a, int bytes) {
    asm volatile("mbarrier.arrive.expect_tx.shared::cta.b64 _, [%0], %1;" ::"r"(a), "r"(bytes) : "memory");
}
__device__ __forceinline__ void mbar_wait(uint32_t a) {
    uint32_t ok;
    int it = 0;
#pragma unroll 1
    do {
        asm volatile("{\n.reg .pred p;\nmbarrier.try_wait.parity.shared::cta.b64 p, [%1], 0;\nselp.u32 %0, 1, 0, p;\n}"
                     : "=r"(ok) : "r"(a) : "memory");
    } while (!ok && ++it < 4096);
}
__device__ __forceinline__ void tma3d(uint32_t dst, const CUtensorMap* m, int c0, int c1, int c2, uint32_t bar) {
    asm volatile("cp.async.bulk.tensor.3d.shared::cluster.global.mbarrier::complete_tx::bytes [%0], [%1, {%3, %4, %5}], [%2];"
                 ::"r"(dst), "l"(m), "r"(bar), "r"(c0), "r"(c1), "r"(c2) : "memory");
}
__device__ __forceinline__ void st_pair(uint32_t dst, uint32_t bar, uint32_t a, uint32_t b) {
#pragma unroll
    for (int r = 0; r < 2; r++) {
        uint32_t d, m;
        asm("mapa.shared::cluster.u32 %0, %1, %2;" : "=r"(d) : "r"(dst), "r"(r));
        asm("mapa.shared::cluster.u32 %0, %1, %2;" : "=r"(m) : "r"(bar), "r"(r));
        asm volatile("st.async.weak.shared::cluster.mbarrier::complete_tx::bytes.v2.b32 [%0], {%1,%2}, [%3];"
                     ::"r"(d), "r"(a), "r"(b), "r"(m) : "memory");
    }
}
__device__ __forceinline__ void cluster_arrive() { asm volatile("barrier.cluster.arrive.relaxed.aligned;" ::: "memory"); }
__device__ __forceinline__ void cluster_wait() { asm volatile("barrier.cluster.wait.acquire.aligned;" ::: "memory"); }
__device__ __forceinline__ void bar_sync(int id, int n) { asm volatile("bar.sync %0, %1;" ::"r"(id), "r"(n) : "memory"); }
__device__ __forceinline__ void bar_arrive(int id, int n) { asm volatile("bar.arrive %0, %1;" ::"r"(id), "r"(n) : "memory"); }
__device__ __forceinline__ void ldsm4(uint32_t (&r)[4], uint32_t a) {
    asm volatile("ldmatrix.sync.aligned.m8n8.x4.shared.b16 {%0,%1,%2,%3}, [%4];"
                 : "=r"(r[0]), "=r"(r[1]), "=r"(r[2]), "=r"(r[3]) : "r"(a) : "memory");
}
__device__ __forceinline__ void ldsm4t(uint32_t (&r)[4], uint32_t a) {
    asm volatile("ldmatrix.sync.aligned.m8n8.x4.trans.shared.b16 {%0,%1,%2,%3}, [%4];"
                 : "=r"(r[0]), "=r"(r[1]), "=r"(r[2]), "=r"(r[3]) : "r"(a) : "memory");
}
__device__ __forceinline__ void mma(float (&c)[4], uint32_t a0, uint32_t a1, uint32_t a2, uint32_t a3, uint32_t b0, uint32_t b1) {
    asm volatile("mma.sync.aligned.m16n8k16.row.col.f32.bf16.bf16.f32 {%0,%1,%2,%3}, {%4,%5,%6,%7}, {%8,%9}, {%0,%1,%2,%3};"
                 : "+f"(c[0]), "+f"(c[1]), "+f"(c[2]), "+f"(c[3])
                 : "r"(a0), "r"(a1), "r"(a2), "r"(a3), "r"(b0), "r"(b1));
}
__device__ __forceinline__ uint4 ld_poll4(const void* p) {
    uint4 v;
    asm volatile("ld.relaxed.gpu.global.v4.u32 {%0,%1,%2,%3}, [%4];" : "=r"(v.x), "=r"(v.y), "=r"(v.z), "=r"(v.w) : "l"(p) : "memory");
    return v;
}
__device__ __forceinline__ uint2 ld_poll2(const void* p) {
    uint2 v;
    asm volatile("ld.relaxed.gpu.global.v2.u32 {%0,%1}, [%2];" : "=r"(v.x), "=r"(v.y) : "l"(p) : "memory");
    return v;
}
__device__ __forceinline__ void st_pub1(void* p, uint32_t v) { asm volatile("st.relaxed.gpu.global.u32 [%0], %1;" ::"l"(p), "r"(v) : "memory"); }
__device__ __forceinline__ void st_pub2(void* p, uint32_t a, uint32_t b) {
    asm volatile("st.relaxed.gpu.global.v2.u32 [%0], {%1,%2};" ::"l"(p), "r"(a), "r"(b) : "memory");
}
__device__ __forceinline__ bool tagged(uint4 v, uint32_t tag) { return (((v.x ^ tag) | (v.y ^ tag) | (v.z ^ tag) | (v.w ^ tag)) & TAGM) == 0; }
__device__ __forceinline__ void delay(uint32_t cycles) {
    uint32_t t0, t1;
    asm volatile("mov.u32 %0, %%clock;" : "=r"(t0));
    do { asm volatile("mov.u32 %0, %%clock;" : "=r"(t1)); } while (t1 - t0 < cycles);
}
__device__ __forceinline__ uint32_t now_ns() { uint32_t t; asm volatile("mov.u32 %0, %%globaltimer_lo;" : "=r"(t)); return t; }
__device__ __forceinline__ unsigned long long to_fix(float v) { return ((unsigned long long)__float2ll_rn(v * 68719476736.f) & ~255ull) | 1ull; }
__device__ __forceinline__ float from_fix(unsigned long long a) { return __ll2float_rn((long long)a) * (1.f / 68719476736.f); }
__device__ __forceinline__ uint32_t tagf(float f, uint32_t tag) { return (__float_as_uint(f) & ~TAGM) | tag; }
__device__ __forceinline__ float untag(uint32_t u) { return __uint_as_float(u & ~TAGM); }
__device__ __forceinline__ float bfr(float f) { return __bfloat162float(__float2bfloat16_rn(f)); }
__device__ __forceinline__ float bflo(uint32_t u) { return __uint_as_float(u << 16); }
__device__ __forceinline__ float bfhi(uint32_t u) { return __uint_as_float(u & 0xffff0000u); }
__device__ __forceinline__ uint32_t pack_bf(float lo, float hi) {
    __nv_bfloat162 v = __floats2bfloat162_rn(lo, hi);
    return *reinterpret_cast<uint32_t*>(&v);
}
__device__ __forceinline__ float sel4(int t, float a, float b, float c, float d) { return (t & 2) ? ((t & 1) ? d : c) : ((t & 1) ? b : a); }

__global__ void __cluster_dims__(2, 1, 1) __launch_bounds__(NTHREADS, 1)
fused_decode_kernel(const __nv_bfloat16* __restrict__ x, const __nv_bfloat16* __restrict__ wq,
                    __nv_bfloat16* __restrict__ out, const __grid_constant__ Maps maps) {
    extern __shared__ __align__(1024) uint8_t smem[];
    const uint32_t sb = (uint32_t)__cvta_generic_to_shared(smem);
    const int tid = threadIdx.x, lane = tid & 31;
    const int warp = tid >> 5;
    const int cta = blockIdx.x, h = cta >> 4, j = cta & 15, pair = cta >> 1, rank = cta & 1;
    const uint32_t bars = sb + SM_BAR;
    const bool has_ffn = cta < NFFN;

    if (warp == 8) {
        const uint32_t t_start = now_ns() - 280;
        uint32_t due = t_start + T_FIRST + cta * T_ALL / NCTA;
        const int u = (!has_ffn && lane >= 8) ? lane + 3 : lane;
        if (lane == 0) {
#pragma unroll
            for (int i = 0; i < 17; i++)
                if (i < 13 || i > 14) mbar_init(bars + 8 * i, 1);
            mbar_expect(bars + 120, 4096);
            mbar_expect(bars + 128, 128);
        }
        asm volatile("fence.proxy.async.shared::cta;" ::: "memory");
        __syncwarp();
        const int mi = u < 8 ? (u >> 2) : min(u - 6, 5);
        const int c0 = (u == 8 || u == 9) ? pair * 32 : 0;
        const int c1 = u < 8 ? h * SK + (SK - WIN) + (u & 3) * 1024 + j * 64 : (u < 10 ? 0 : (u == 10 ? pair * 32 : pair * 64 + (u - 11) * 32));
        const int c2 = u < 8 ? 0 : (u < 10 ? rank : 4 * rank);
        const uint32_t dst = sb + (u < 11 ? SM_K + u * 16384 : SM_W + (u - 11) * 16384);
        const int n = has_ffn ? 13 : 10;
        asm volatile("fence.mbarrier_init.release.cluster;" ::: "memory");
        cluster_arrive();
        bar_arrive(1, NTHREADS);
#pragma unroll 1
        for (int i = 0; i < n; i++) {
            if (i == NFREE) bar_sync(5, 96);
            if (i == n - 2) {
                bar_sync(2, 288);
                asm volatile("fence.proxy.async.shared::cta;" ::: "memory");
            }
            if (i >= NFREE) mbar_wait(bars + 8 * (int)((DEP >> (48 - 4 * i)) & 15));
            for (int it = 0; it < 1024 && (int)(now_ns() - due) < 0; it++) {}
            due += (i < 7 || (i == 7 && has_ffn)) ? T_ALL : (has_ffn ? T_FFN : T_NOFFN);
            if (lane == i) {
                mbar_expect(bars + 8 * u, 16384);
                tma3d(dst, &maps.m[mi], c0, c1, c2, bars + 8 * u);
            }
            __syncwarp();
        }
        return;
    }
    if (warp == 9) {
        const uint32_t tag = __ldcg(&g_epoch);
        cluster_arrive();
        if (lane == 0) *reinterpret_cast<uint32_t*>(smem + SM_TAG) = tag;
        bar_arrive(1, NTHREADS);
        cluster_wait();
        {
            const uint2* pml = g_ml + (h * 16 + (lane >> 3)) * 4 + (j >> 2);
            const uint4* po = reinterpret_cast<const uint4*>(g_o + cta * 512) + lane;
            uint2 ml[4];
            uint4 v[4];
            bar_sync(7, 64);
            delay(O_DELAY);
#pragma unroll
            for (int i = 0; i < 4; i++) ml[i] = ld_poll2(pml + 16 * i);
#pragma unroll
            for (int i = 0; i < 4; i++) v[i] = ld_poll4(po + 32 * i);
#pragma unroll 1
            for (int it = 0; it < SPIN_LIMIT; it++) {
                bool ok = true;
#pragma unroll
                for (int i = 0; i < 4; i++) {
                    if (!tagged(v[i], tag)) { v[i] = ld_poll4(po + 32 * i); ok = false; }
                    if (((ml[i].x ^ tag) | (ml[i].y ^ tag)) & TAGM) { ml[i] = ld_poll2(pml + 16 * i); ok = false; }
                }
                if (__all_sync(~0u, ok)) break;
            }
            float M = fmaxf(fmaxf(untag(ml[0].x), untag(ml[1].x)), fmaxf(untag(ml[2].x), untag(ml[3].x)));
            M = fmaxf(M, __shfl_xor_sync(~0u, M, 8));
            M = fmaxf(M, __shfl_xor_sync(~0u, M, 16));
            float a0 = 0.f, a1 = 0.f, a2 = 0.f, a3 = 0.f, L = 0.f;
#pragma unroll
            for (int i = 0; i < 4; i++) {
                const float w = __expf(untag(ml[i].x) - M);
                L += w * untag(ml[i].y);
                a0 += w * untag(v[i].x); a1 += w * untag(v[i].y);
                a2 += w * untag(v[i].z); a3 += w * untag(v[i].w);
            }
#pragma unroll
            for (int s = 8; s < 32; s <<= 1) {
                L += __shfl_xor_sync(~0u, L, s);
                a0 += __shfl_xor_sync(~0u, a0, s); a1 += __shfl_xor_sync(~0u, a1, s);
                a2 += __shfl_xor_sync(~0u, a2, s); a3 += __shfl_xor_sync(~0u, a3, s);
            }
            L = __fdividef(1.f, L);
            if (lane < 8) st_pair(sb + SM_O + rank * 64 + lane * 8, bars + 128, pack_bf(a0 * L, a1 * L), pack_bf(a2 * L, a3 * L));
        }
        return;
    }

    const int g = lane >> 2, t = lane & 3;
    const int lrow = (lane & 7) + ((lane >> 4) << 3);
    const int lch = (lane >> 3) & 1;
    {
        uint32_t ofs = (warp * 32 + g) * 8192 + cta * 64 + t * 16;
        uint32_t dst = sb + SM_W + (warp * 64 + g) * 64 + ((t ^ ((g >> 1) & 3)) << 4);
        asm volatile("" : "+r"(ofs), "+r"(dst));
        if ((ofs ^ dst) == 1u) return;
        const char* src = reinterpret_cast<const char*>(wq) + ofs;
#pragma unroll
        for (int i = 0; i < 8; i++)
            asm volatile("cp.async.cg.shared.global.L2::128B [%0], [%1], 16;" ::"r"(dst + i * 512), "l"(src + (size_t)((i >> 2) * 32 + (i & 3)) * 65536) : "memory");
        if ((warp & 3) == 3) {
            const uint32_t b = bars + 8 * (13 + (warp >> 2));
            if (lane == 0) mbar_init(b, 32);
            __syncwarp();
            asm volatile("cp.async.mbarrier.arrive.noinc.shared::cta.b64 [%0];" ::"r"(b) : "memory");
            bar_arrive(5, 96);
        }
    }
    cluster_arrive();
    uint32_t xn[8];
    uint32_t* const pqo = g_q + cta * 32 + lane;
    uint2* const pml = g_ml + cta * 4 + (g & 3);
    uint32_t* const po = g_o + ((h * 16 + (t & 1) * 8 + (warp >> 1)) * 16 + j) * 32 + (warp & 1) * 16 + (t >> 1) * 8 + g;
    unsigned long long* const pa = g_acc + (rank * 32 + (tid >> 3)) * 32 + (tid & 7);
    const int ocol = 256 * rank + 32 * warp + 8 * t + g;
    {
        const uint4 xa = __ldg(reinterpret_cast<const uint4*>(x) + lane);
        const uint4 xb = __ldg(reinterpret_cast<const uint4*>(x) + 32 + lane);
#pragma unroll
        for (int i = 0; i < 8; i++) xn[i] = __ldg(reinterpret_cast<const uint32_t*>(x) + (i >> 2) * 128 + warp * 16 + (i & 3) * 4 + t);
        if (pair == (tid >> 2)) atomicAdd(pa, to_fix(__bfloat162float(x[ocol])));
        const uint32_t xw[8] = {xa.x, xa.y, xa.z, xa.w, xb.x, xb.y, xb.z, xb.w};
        float s = 0.f;
#pragma unroll
        for (int i = 0; i < 8; i++) s += bflo(xw[i]) + bfhi(xw[i]);
#pragma unroll
        for (int o = 1; o < 32; o <<= 1) s += __shfl_xor_sync(~0u, s, o);
        const float mean = s * (1.f / D_MODEL);
        float q = 0.f;
#pragma unroll
        for (int i = 0; i < 8; i++) {
            const float a = bflo(xw[i]) - mean, b = bfhi(xw[i]) - mean;
            q += a * a + b * b;
        }
#pragma unroll
        for (int o = 1; o < 32; o <<= 1) q += __shfl_xor_sync(~0u, q, o);
        const float mb = bfr(mean);
        float sd;
        asm("sqrt.approx.f32 %0, %1;" : "=f"(sd) : "f"(bfr(bfr(q * (1.f / D_MODEL)) + 1e-5f)));
        const float rden = __fdividef(1.f, bfr(sd));
#pragma unroll
        for (int i = 0; i < 8; i++) xn[i] = pack_bf(bfr(bflo(xn[i]) - mb) * rden, bfr(bfhi(xn[i]) - mb) * rden);
    }
    asm volatile("cp.async.wait_all;" ::: "memory");
    __syncwarp();
    {
        float c0[4] = {0.f, 0.f, 0.f, 0.f}, c1[4] = {0.f, 0.f, 0.f, 0.f};
        const uint32_t base = sb + SM_W + (warp * 64 + lrow) * 64;
        const int sw = (lane >> 1) & 3;
#pragma unroll
        for (int s = 0; s < 4; s++) {
            uint32_t a[4], b[4];
            ldsm4t(a, base + s * 1024 + ((lch ^ sw) << 4));
            ldsm4t(b, base + s * 1024 + (((2 + lch) ^ sw) << 4));
            mma(c0, a[0], a[1], a[2], a[3], xn[2 * s], xn[2 * s + 1]);
            mma(c1, b[0], b[1], b[2], b[3], xn[2 * s], xn[2 * s + 1]);
        }
        reinterpret_cast<float*>(smem + SM_PART)[warp * 32 + 8 * t + g] = sel4(t, c0[0], c0[2], c1[0], c1[2]);
    }
    bar_arrive(2, 288);
    bar_sync(1, NTHREADS);
    const uint32_t tag = *reinterpret_cast<const uint32_t*>(smem + SM_TAG);
    if (warp == 0) {
        float s = 0.f;
#pragma unroll
        for (int w = 0; w < 8; w++) s += reinterpret_cast<const float*>(smem + SM_PART)[w * 32 + lane];
        st_pub1(pqo, __float_as_uint(bfr(s)) | tag);
    }
    if (tid < 128) {
        const uint4* pq = reinterpret_cast<const uint4*>(g_q + h * 512) + tid;
        uint4 v;
        delay(Q_DELAY);
#pragma unroll 1
        for (int it = 0; it < SPIN_LIMIT; it++) {
            v = ld_poll4(pq);
            if (tagged(v, tag)) break;
        }
        *reinterpret_cast<uint2*>(smem + SM_Q + warp * 272 + lane * 8) =
            make_uint2(__byte_perm(v.x, v.y, 0x7632), __byte_perm(v.z, v.w, 0x7632));
    }
    bar_sync(3, 256);
    const int head = g & 3;
    float sc[4];
    {
        uint32_t qa[4][4];
#pragma unroll
        for (int i = 0; i < 4; i++) ldsm4(qa[i], sb + SM_Q + (lane & 3) * 272 + (4 * i + (lane >> 3)) * 16);
        mbar_wait(bars + 8 * (warp >> 1));
        float c[4][4];
        const uint32_t kb = sb + SM_K + (warp >> 1) * 16384 + (32 * (warp & 1) + (lane & 7)) * 128;
#pragma unroll
        for (int n = 0; n < 4; n++) {
#pragma unroll
            for (int e = 0; e < 4; e++) c[n][e] = 0.f;
#pragma unroll
            for (int i = 0; i < 4; i++) {
                uint32_t b[4];
                ldsm4(b, kb + n * 1024 + (i >> 1) * 8192 + (((4 * (i & 1) + (lane >> 3)) ^ (lane & 7)) << 4));
                mma(c[n], qa[i][0], 0u, qa[i][1], 0u, b[0], b[1]);
                mma(c[n], qa[i][2], 0u, qa[i][3], 0u, b[2], b[3]);
            }
        }
        const bool up = g >= 4;
        const float scale = 0.08838834764831845f;
        sc[0] = bfr(bfr(up ? c[2][0] : c[0][0]) * scale);
        sc[1] = bfr(bfr(up ? c[2][1] : c[0][1]) * scale);
        sc[2] = bfr(bfr(up ? c[3][0] : c[1][0]) * scale);
        sc[3] = bfr(bfr(up ? c[3][1] : c[1][1]) * scale);
    }
    float mcta;
    {
        float m = fmaxf(fmaxf(sc[0], sc[1]), fmaxf(sc[2], sc[3]));
        m = fmaxf(m, __shfl_xor_sync(~0u, m, 1));
        m = fmaxf(m, __shfl_xor_sync(~0u, m, 2));
        m = fmaxf(m, __shfl_xor_sync(~0u, m, 16));
        if (t == 0 && g < 4) reinterpret_cast<float*>(smem + SM_MX)[g * 8 + warp] = m;
        bar_sync(3, 256);
        const float4 m0 = *reinterpret_cast<const float4*>(smem + SM_MX + head * 32);
        const float4 m1 = *reinterpret_cast<const float4*>(smem + SM_MX + head * 32 + 16);
        mcta = fmaxf(fmaxf(fmaxf(m0.x, m0.y), fmaxf(m0.z, m0.w)), fmaxf(fmaxf(m1.x, m1.y), fmaxf(m1.z, m1.w)));
        const float p0 = __expf(sc[0] - mcta), p1 = __expf(sc[1] - mcta), p2 = __expf(sc[2] - mcta), p3 = __expf(sc[3] - mcta);
        uint8_t* pp = smem + SM_P + head * 528 + (32 * warp + 16 * (g >> 2) + 2 * t) * 2;
        *reinterpret_cast<uint32_t*>(pp) = pack_bf(p0, p1);
        *reinterpret_cast<uint32_t*>(pp + 16) = pack_bf(p2, p3);
        float l = (p0 + p1) + (p2 + p3);
        l += __shfl_xor_sync(~0u, l, 1);
        l += __shfl_xor_sync(~0u, l, 2);
        l += __shfl_xor_sync(~0u, l, 16);
        if (t == 0 && g < 4) reinterpret_cast<float*>(smem + SM_SUM)[g * 8 + warp] = l;
        bar_sync(3, 256);
        if (warp == 0 && t == 0 && g < 4) {
            const float4 l0 = *reinterpret_cast<const float4*>(smem + SM_SUM + head * 32);
            const float4 l1 = *reinterpret_cast<const float4*>(smem + SM_SUM + head * 32 + 16);
            const float ls = ((l0.x + l0.y) + (l0.z + l0.w)) + ((l1.x + l1.y) + (l1.z + l1.w));
            st_pub2(pml, tagf(mcta, tag), tagf(ls, tag));
        }
    }
    {
        float c0[4] = {0.f, 0.f, 0.f, 0.f}, c1[4] = {0.f, 0.f, 0.f, 0.f};
        const uint32_t pb = sb + SM_P + (lane & 3) * 528 + (lane >> 3) * 16;
        const uint32_t vb = sb + SM_V + (warp >> 2) * 8192 + lrow * 128 + (((2 * (warp & 3) + lch) ^ (lane & 7)) << 4);
#pragma unroll
        for (int i = 0; i < 4; i++) {
            uint32_t p0[4], p1[4], a[4][4];
            ldsm4(p0, pb + i * 128);
            ldsm4(p1, pb + i * 128 + 64);
            mbar_wait(bars + 32 + 8 * i);
#pragma unroll
            for (int s = 0; s < 4; s++) ldsm4t(a[s], vb + i * 16384 + s * 2048);
            mma(c0, a[0][0], a[0][1], a[0][2], a[0][3], p0[0], p0[1]);
            mma(c1, a[1][0], a[1][1], a[1][2], a[1][3], p0[2], p0[3]);
            mma(c0, a[2][0], a[2][1], a[2][2], a[2][3], p1[0], p1[1]);
            mma(c1, a[3][0], a[3][1], a[3][2], a[3][3], p1[2], p1[3]);
        }
        const bool up = t >= 2;
        const float v0 = up ? c0[2] + c1[2] : c0[0] + c1[0];
        const float v1 = up ? c0[3] + c1[3] : c0[1] + c1[1];
        st_pub1(po, tagf(v0, tag));
        st_pub1(po + 4 * 512, tagf(v1, tag));
        if (warp == 0) bar_arrive(7, 64);
    }
    float y0[4] = {0.f, 0.f, 0.f, 0.f}, y1[4] = {0.f, 0.f, 0.f, 0.f};
    const uint32_t wofs = (warp >> 1) * 4096 + lrow * 128 + (((4 * (warp & 1) + lch) ^ (lane & 7)) << 4);
    if (has_ffn) {
        float c[4][4];
        const uint32_t base = sb + SM_G + (warp * 32 + lrow) * 64 + ((lch ^ ((lane >> 1) & 3)) << 4);
        const uint32_t x0 = rank ? xn[4] : xn[0], x1 = rank ? xn[5] : xn[1], x2 = rank ? xn[6] : xn[2], x3 = rank ? xn[7] : xn[3];
        cluster_wait();
#pragma unroll
        for (int m = 0; m < 4; m++) {
            uint32_t a[4], b[4];
            if (!(m & 1)) mbar_wait(bars + 64 + 4 * m);
            ldsm4t(a, (base ^ ((m & 1) << 5)) + (m >> 1) * 16384);
            ldsm4t(b, (base ^ ((m & 1) << 5)) + (m >> 1) * 16384 + 1024);
#pragma unroll
            for (int e = 0; e < 4; e++) c[m][e] = 0.f;
            mma(c[m], a[0], a[1], a[2], a[3], x0, x1);
            mma(c[m], b[0], b[1], b[2], b[3], x2, x3);
        }
        st_pair(sb + SM_PART2 + (rank * 8 + warp) * 256 + (8 * t + g) * 8, bars + 120,
                __float_as_uint(sel4(t, c[0][0], c[0][2], c[1][0], c[1][2])), __float_as_uint(sel4(t, c[2][0], c[2][2], c[3][0], c[3][2])));
        mbar_wait(bars + 120);
        float gs = 0.f, us = 0.f;
#pragma unroll
        for (int w = 0; w < 16; w++) {
            const float2 v = reinterpret_cast<const float2*>(smem + SM_PART2)[w * 32 + lane];
            gs += v.x;
            us += v.y;
        }
        gs = bfr(gs);
        const float hv = bfr(__fdividef(gs, 1.f + __expf(-gs))) * bfr(us);
        const uint32_t hp = pack_bf(hv, __shfl_down_sync(~0u, hv, 1));
        uint32_t hb[4];
#pragma unroll
        for (int i = 0; i < 4; i++) hb[i] = __shfl_sync(~0u, hp, 8 * i + 2 * t);
        mbar_wait(bars + 80);
#pragma unroll
        for (int s = 0; s < 2; s++) {
            uint32_t a[4], b[4];
            ldsm4t(a, sb + SM_D + s * 2048 + wofs);
            ldsm4t(b, sb + SM_D + s * 2048 + (wofs ^ 32));
            mma(y0, a[0], a[1], a[2], a[3], hb[2 * s], hb[2 * s + 1]);
            mma(y1, b[0], b[1], b[2], b[3], hb[2 * s], hb[2 * s + 1]);
        }
    }
    mbar_wait(bars + 128);
    {
        uint32_t ob[8];
#pragma unroll
        for (int i = 0; i < 8; i++) ob[i] = *reinterpret_cast<const uint32_t*>(smem + SM_O + i * 16 + t * 4);
        __nv_bfloat16* pout = out + ocol;
        asm volatile("" : "+l"(pout));
        float z0[4] = {0.f, 0.f, 0.f, 0.f}, z1[4] = {0.f, 0.f, 0.f, 0.f};
#pragma unroll
        for (int s = 0; s < 4; s++) {
            uint32_t a[4], b[4];
            if (!(s & 1)) mbar_wait(bars + 88 + 4 * s);
            ldsm4t(a, sb + SM_W + (s >> 1) * 16384 + (s & 1) * 2048 + wofs);
            ldsm4t(b, sb + SM_W + (s >> 1) * 16384 + (s & 1) * 2048 + (wofs ^ 32));
            mma((s & 1) ? z0 : y0, a[0], a[1], a[2], a[3], ob[2 * s], ob[2 * s + 1]);
            mma((s & 1) ? z1 : y1, b[0], b[1], b[2], b[3], ob[2 * s], ob[2 * s + 1]);
        }
        const unsigned long long f = to_fix(sel4(t, y0[0], y0[2], y1[0], y1[2]) + sel4(t, z0[0], z0[2], z1[0], z1[2]));
        const unsigned long long a = atomicAdd(pa, f) + (f - (NCTA / 2 + 1));
        if (((uint32_t)a & 255u) == 0) {
            asm volatile("st.global.u16 [%0], %1;" ::"l"(pout), "h"(__bfloat16_as_ushort(__float2bfloat16_rn(from_fix(a)))) : "memory");
            *pa = 0;
            if (ocol == 0) g_epoch = tag == TAGM ? 1u : tag + 1;
        }
    }
}

typedef CUresult (*EncodeFn)(CUtensorMap*, CUtensorMapDataType, cuuint32_t, void*, const cuuint64_t*, const cuuint64_t*,
                             const cuuint32_t*, const cuuint32_t*, CUtensorMapInterleave, CUtensorMapSwizzle,
                             CUtensorMapL2promotion, CUtensorMapFloatOOBfill);

void make_map(EncodeFn enc, CUtensorMap* m, void* p, uint64_t d0, uint64_t d1, uint64_t d2, uint64_t s1, uint64_t s2,
              uint32_t b0, uint32_t b1, uint32_t b2, CUtensorMapSwizzle sw) {
    cuuint64_t gd[3] = {d0, d1, d2};
    cuuint64_t gs[2] = {s1, s2};
    cuuint32_t bd[3] = {b0, b1, b2};
    cuuint32_t es[3] = {1, 1, 1};
    enc(m, CU_TENSOR_MAP_DATA_TYPE_BFLOAT16, 3, p, gd, gs, bd, es, CU_TENSOR_MAP_INTERLEAVE_NONE, sw,
        CU_TENSOR_MAP_L2_PROMOTION_L2_128B, CU_TENSOR_MAP_FLOAT_OOB_FILL_NONE);
}

}

extern "C" void kernel_launch(void* const* d_in, const int* in_sizes, int n_in, void* d_out, int out_size) {
    static EncodeFn enc = nullptr;
    if (!enc) {
        void* fn = nullptr;
        cudaDriverEntryPointQueryResult qr;
        cudaGetDriverEntryPoint("cuTensorMapEncodeTiled", &fn, cudaEnableDefault, &qr);
        enc = (EncodeFn)fn;
        cudaFuncSetAttribute(fused_decode_kernel, cudaFuncAttributeMaxDynamicSharedMemorySize, SM_TOTAL);
    }
    Maps m;
    make_map(enc, &m.m[0], d_in[1], 64, (uint64_t)HKV * SK, 2, DH * 2, 128, 64, 64, 2, CU_TENSOR_MAP_SWIZZLE_128B);
    make_map(enc, &m.m[1], d_in[2], 64, (uint64_t)HKV * SK, 2, DH * 2, 128, 64, 64, 2, CU_TENSOR_MAP_SWIZZLE_128B);
    make_map(enc, &m.m[2], d_in[6], FF, 256, 2, FF * 2, FF * 2 * 256, 32, 256, 1, CU_TENSOR_MAP_SWIZZLE_64B);
    make_map(enc, &m.m[3], d_in[7], FF, 256, 2, FF * 2, FF * 2 * 256, 32, 256, 1, CU_TENSOR_MAP_SWIZZLE_64B);
    make_map(enc, &m.m[4], d_in[8], 64, FF, 8, D_MODEL * 2, 128, 64, 32, 4, CU_TENSOR_MAP_SWIZZLE_128B);
    make_map(enc, &m.m[5], d_in[4], 64, 4096, 8, D_MODEL * 2, 128, 64, 32, 4, CU_TENSOR_MAP_SWIZZLE_128B);
    fused_decode_kernel<<<NCTA, NTHREADS, SM_TOTAL>>>((const __nv_bfloat16*)d_in[0], (const __nv_bfloat16*)d_in[3],
                                                      (__nv_bfloat16*)d_out, m);
}
```

```cpp
#include <cuda_runtime.h>
#include <cuda_bf16.h>
#include <cuda.h>
#include <stdint.h>

namespace {

constexpr int D_MODEL = 512, HKV = 8, SK = 65536, DH = 128, WIN = 4096, FF = 1792;
constexpr int NCTA = 128, NFFN = FF / 16, NTHREADS = 320;
constexpr unsigned long long DEP = 0xFFDE012345678ull;
constexpr int NFREE = 2;
constexpr int T_FIRST = 640, T_ALL = 672, T_FFN = 600, T_NOFFN = 1500;
constexpr int Q_DELAY = 2000, O_DELAY = 1750;
constexpr uint32_t TAGM = 7u;
constexpr int SPIN_LIMIT = 1 << 20;

constexpr int SM_W = 0;
constexpr int SM_K = 32768;
constexpr int SM_V = SM_K + 65536;
constexpr int SM_G = SM_V + 65536;
constexpr int SM_U = SM_G + 16384;
constexpr int SM_D = SM_U + 16384;
constexpr int SM_BAR = SM_D + 16384;
constexpr int SM_TAG = SM_BAR + 192;
constexpr int SM_PART = SM_BAR + 256;
constexpr int SM_Q = SM_PART + 1024;
constexpr int SM_P = SM_Q + 1088;
constexpr int SM_MX = SM_P + 2112;
constexpr int SM_SUM = SM_MX + 128;
constexpr int SM_O = SM_SUM + 128;
constexpr int SM_PART2 = SM_O + 128;
constexpr int SM_TOTAL = SM_PART2 + 4096;

struct __align__(64) Maps { CUtensorMap m[6]; };

__device__ uint32_t g_epoch = 1;
__device__ __align__(128) uint32_t g_q[NCTA * 32];
__device__ __align__(128) uint32_t g_o[NCTA * 16 * 32];
__device__ __align__(128) uint2 g_ml[HKV * 4 * 16];
__device__ __align__(128) unsigned long long g_acc[D_MODEL / 8 * 32];

__device__ __forceinline__ void mbar_init(uint32_t a, int n) { asm volatile("mbarrier.init.shared::cta.b64 [%0], %1;" ::"r"(a), "r"(n) : "memory"); }
__device__ __forceinline__ void mbar_expect(uint32_t a, int bytes) {
    asm volatile("mbarrier.arrive.expect_tx.shared::cta.b64 _, [%0], %1;" ::"r"(a), "r"(bytes) : "memory");
}
__device__ __forceinline__ void mbar_wait(uint32_t a) {
    uint32_t ok;
    int it = 0;
#pragma unroll 1
    do {
        asm volatile("{\n.reg .pred p;\nmbarrier.try_wait.parity.shared::cta.b64 p, [%1], 0;\nselp.u32 %0, 1, 0, p;\n}"
                     : "=r"(ok) : "r"(a) : "memory");
    } while (!ok && ++it < 4096);
}
__device__ __forceinline__ void tma3d(uint32_t dst, const CUtensorMap* m, int c0, int c1, int c2, uint32_t bar) {
    asm volatile("cp.async.bulk.tensor.3d.shared::cluster.global.mbarrier::complete_tx::bytes [%0], [%1, {%3, %4, %5}], [%2];"
                 ::"r"(dst), "l"(m), "r"(bar), "r"(c0), "r"(c1), "r"(c2) : "memory");
}
__device__ __forceinline__ void st_pair(uint32_t dst, uint32_t bar, uint32_t a, uint32_t b) {
#pragma unroll
    for (int r = 0; r < 2; r++) {
        uint32_t d, m;
        asm("mapa.shared::cluster.u32 %0, %1, %2;" : "=r"(d) : "r"(dst), "r"(r));
        asm("mapa.shared::cluster.u32 %0, %1, %2;" : "=r"(m) : "r"(bar), "r"(r));
        asm volatile("st.async.weak.shared::cluster.mbarrier::complete_tx::bytes.v2.b32 [%0], {%1,%2}, [%3];"
                     ::"r"(d), "r"(a), "r"(b), "r"(m) : "memory");
    }
}
__device__ __forceinline__ void cluster_arrive() { asm volatile("barrier.cluster.arrive.relaxed.aligned;" ::: "memory"); }
__device__ __forceinline__ void cluster_wait() { asm volatile("barrier.cluster.wait.acquire.aligned;" ::: "memory"); }
__device__ __forceinline__ void bar_sync(int id, int n) { asm volatile("bar.sync %0, %1;" ::"r"(id), "r"(n) : "memory"); }
__device__ __forceinline__ void bar_arrive(int id, int n) { asm volatile("bar.arrive %0, %1;" ::"r"(id), "r"(n) : "memory"); }
__device__ __forceinline__ void ldsm4(uint32_t (&r)[4], uint32_t a) {
    asm volatile("ldmatrix.sync.aligned.m8n8.x4.shared.b16 {%0,%1,%2,%3}, [%4];"
                 : "=r"(r[0]), "=r"(r[1]), "=r"(r[2]), "=r"(r[3]) : "r"(a) : "memory");
}
__device__ __forceinline__ void ldsm4t(uint32_t (&r)[4], uint32_t a) {
    asm volatile("ldmatrix.sync.aligned.m8n8.x4.trans.shared.b16 {%0,%1,%2,%3}, [%4];"
                 : "=r"(r[0]), "=r"(r[1]), "=r"(r[2]), "=r"(r[3]) : "r"(a) : "memory");
}
__device__ __forceinline__ void mma(float (&c)[4], uint32_t a0, uint32_t a1, uint32_t a2, uint32_t a3, uint32_t b0, uint32_t b1) {
    asm volatile("mma.sync.aligned.m16n8k16.row.col.f32.bf16.bf16.f32 {%0,%1,%2,%3}, {%4,%5,%6,%7}, {%8,%9}, {%0,%1,%2,%3};"
                 : "+f"(c[0]), "+f"(c[1]), "+f"(c[2]), "+f"(c[3])
                 : "r"(a0), "r"(a1), "r"(a2), "r"(a3), "r"(b0), "r"(b1));
}
__device__ __forceinline__ uint4 ld_poll4(const void* p) {
    uint4 v;
    asm volatile("ld.relaxed.gpu.global.v4.u32 {%0,%1,%2,%3}, [%4];" : "=r"(v.x), "=r"(v.y), "=r"(v.z), "=r"(v.w) : "l"(p) : "memory");
    return v;
}
__device__ __forceinline__ uint2 ld_poll2(const void* p) {
    uint2 v;
    asm volatile("ld.relaxed.gpu.global.v2.u32 {%0,%1}, [%2];" : "=r"(v.x), "=r"(v.y) : "l"(p) : "memory");
    return v;
}
__device__ __forceinline__ void st_pub1(void* p, uint32_t v) { asm volatile("st.relaxed.gpu.global.u32 [%0], %1;" ::"l"(p), "r"(v) : "memory"); }
__device__ __forceinline__ void st_pub2(void* p, uint32_t a, uint32_t b) {
    asm volatile("st.relaxed.gpu.global.v2.u32 [%0], {%1,%2};" ::"l"(p), "r"(a), "r"(b) : "memory");
}
__device__ __forceinline__ bool tagged(uint4 v, uint32_t tag) { return (((v.x ^ tag) | (v.y ^ tag) | (v.z ^ tag) | (v.w ^ tag)) & TAGM) == 0; }
__device__ __forceinline__ void delay(uint32_t cycles) {
    uint32_t t0, t1, it = 0;
    asm volatile("mov.u32 %0, %%clock;" : "=r"(t0));
#pragma unroll 1
    do { asm volatile("mov.u32 %0, %%clock;" : "=r"(t1)); } while (t1 - t0 < cycles && ++it < cycles);
}
__device__ __forceinline__ uint32_t now_ns() { uint32_t t; asm volatile("mov.u32 %0, %%globaltimer_lo;" : "=r"(t)); return t; }
__device__ __forceinline__ unsigned long long to_fix(float v) { return ((unsigned long long)__float2ll_rn(v * 68719476736.f) & ~255ull) | 1ull; }
__device__ __forceinline__ float from_fix(unsigned long long a) { return __ll2float_rn((long long)a) * (1.f / 68719476736.f); }
__device__ __forceinline__ uint32_t tagf(float f, uint32_t tag) { return (__float_as_uint(f) & ~TAGM) | tag; }
__device__ __forceinline__ float untag(uint32_t u) { return __uint_as_float(u & ~TAGM); }
__device__ __forceinline__ float bfr(float f) { return __bfloat162float(__float2bfloat16_rn(f)); }
__device__ __forceinline__ float bflo(uint32_t u) { return __uint_as_float(u << 16); }
__device__ __forceinline__ float bfhi(uint32_t u) { return __uint_as_float(u & 0xffff0000u); }
__device__ __forceinline__ uint32_t pack_bf(float lo, float hi) {
    __nv_bfloat162 v = __floats2bfloat162_rn(lo, hi);
    return *reinterpret_cast<uint32_t*>(&v);
}
__device__ __forceinline__ float sel4(int t, float a, float b, float c, float d) { return (t & 2) ? ((t & 1) ? d : c) : ((t & 1) ? b : a); }

__global__ void __cluster_dims__(2, 1, 1) __launch_bounds__(NTHREADS, 1)
fused_decode_kernel(const __nv_bfloat16* __restrict__ x, const __nv_bfloat16* __restrict__ wq,
                    __nv_bfloat16* __restrict__ out, const __grid_constant__ Maps maps) {
    extern __shared__ __align__(1024) uint8_t smem[];
    const uint32_t sb = (uint32_t)__cvta_generic_to_shared(smem);
    const int tid = threadIdx.x, lane = tid & 31;
    const int warp = tid >> 5;
    const int cta = blockIdx.x, h = cta >> 4, j = cta & 15, pair = cta >> 1, rank = cta & 1;
    const uint32_t bars = sb + SM_BAR;
    const bool has_ffn = cta < NFFN;

    if (warp == 8) {
        uint32_t due = now_ns() + T_FIRST + cta * T_ALL / NCTA;
        const int u = (!has_ffn && lane >= 8) ? lane + 3 : lane;
        if (lane == 0) {
#pragma unroll
            for (int i = 0; i < 17; i++)
                if (i < 13 || i > 14) mbar_init(bars + 8 * i, 1);
            mbar_expect(bars + 120, 4096);
            mbar_expect(bars + 128, 128);
        }
        asm volatile("fence.proxy.async.shared::cta;" ::: "memory");
        __syncwarp();
        const int mi = u < 8 ? (u >> 2) : min(u - 6, 5);
        const int c0 = (u == 8 || u == 9) ? pair * 32 : 0;
        const int c1 = u < 8 ? h * SK + (SK - WIN) + (u & 3) * 1024 + j * 64 : (u < 10 ? 0 : (u == 10 ? pair * 32 : pair * 64 + (u - 11) * 32));
        const int c2 = u < 8 ? 0 : (u < 10 ? rank : 4 * rank);
        const uint32_t dst = sb + (u < 11 ? SM_K + u * 16384 : SM_W + (u - 11) * 16384);
        const int n = has_ffn ? 13 : 10;
        asm volatile("fence.mbarrier_init.release.cluster;" ::: "memory");
        cluster_arrive();
        bar_arrive(1, NTHREADS);
#pragma unroll 1
        for (int i = 0; i < n; i++) {
            if (i == NFREE) bar_sync(5, 96);
            if (i == n - 2) {
                bar_sync(2, 288);
                asm volatile("fence.proxy.async.shared::cta;" ::: "memory");
            }
            if (i >= NFREE) mbar_wait(bars + 8 * (int)((DEP >> (48 - 4 * i)) & 15));
            for (int it = 0; it < 1024 && (int)(now_ns() - due) < 0; it++) {}
            due += (i < 7 || (i == 7 && has_ffn)) ? T_ALL : (has_ffn ? T_FFN : T_NOFFN);
            if (lane == i) {
                mbar_expect(bars + 8 * u, 16384);
                tma3d(dst, &maps.m[mi], c0, c1, c2, bars + 8 * u);
            }
            __syncwarp();
        }
        return;
    }
    if (warp == 9) {
        const uint32_t tag = __ldcg(&g_epoch);
        cluster_arrive();
        if (lane == 0) *reinterpret_cast<uint32_t*>(smem + SM_TAG) = tag;
        bar_arrive(1, NTHREADS);
        cluster_wait();
        {
            const uint2* pml = g_ml + (h * 16 + (lane >> 3)) * 4 + (j >> 2);
            const uint4* po = reinterpret_cast<const uint4*>(g_o + cta * 512) + lane;
            uint2 ml[4];
            uint4 v[4];
            bar_sync(7, 64);
            delay(O_DELAY);
#pragma unroll
            for (int i = 0; i < 4; i++) ml[i] = ld_poll2(pml + 16 * i);
#pragma unroll
            for (int i = 0; i < 4; i++) v[i] = ld_poll4(po + 32 * i);
#pragma unroll 1
            for (int it = 0; it < SPIN_LIMIT; it++) {
                bool ok = true;
#pragma unroll
                for (int i = 0; i < 4; i++) {
                    if (!tagged(v[i], tag)) { v[i] = ld_poll4(po + 32 * i); ok = false; }
                    if (((ml[i].x ^ tag) | (ml[i].y ^ tag)) & TAGM) { ml[i] = ld_poll2(pml + 16 * i); ok = false; }
                }
                if (__all_sync(~0u, ok)) break;
            }
            float M = fmaxf(fmaxf(untag(ml[0].x), untag(ml[1].x)), fmaxf(untag(ml[2].x), untag(ml[3].x)));
            M = fmaxf(M, __shfl_xor_sync(~0u, M, 8));
            M = fmaxf(M, __shfl_xor_sync(~0u, M, 16));
            float a0 = 0.f, a1 = 0.f, a2 = 0.f, a3 = 0.f, L = 0.f;
#pragma unroll
            for (int i = 0; i < 4; i++) {
                const float w = __expf(untag(ml[i].x) - M);
                L += w * untag(ml[i].y);
                a0 += w * untag(v[i].x); a1 += w * untag(v[i].y);
                a2 += w * untag(v[i].z); a3 += w * untag(v[i].w);
            }
#pragma unroll
            for (int s = 8; s < 32; s <<= 1) {
                L += __shfl_xor_sync(~0u, L, s);
                a0 += __shfl_xor_sync(~0u, a0, s); a1 += __shfl_xor_sync(~0u, a1, s);
                a2 += __shfl_xor_sync(~0u, a2, s); a3 += __shfl_xor_sync(~0u, a3, s);
            }
            L = __fdividef(1.f, L);
            if (lane < 8) st_pair(sb + SM_O + rank * 64 + lane * 8, bars + 128, pack_bf(a0 * L, a1 * L), pack_bf(a2 * L, a3 * L));
        }
        return;
    }

    const int g = lane >> 2, t = lane & 3;
    const int lrow = (lane & 7) + ((lane >> 4) << 3);
    const int lch = (lane >> 3) & 1;
    {
        uint32_t ofs = (warp * 32 + g) * 8192 + cta * 64 + t * 16;
        uint32_t dst = sb + SM_W + (warp * 64 + g) * 64 + ((t ^ ((g >> 1) & 3)) << 4);
        asm volatile("" : "+r"(ofs), "+r"(dst));
        if ((ofs ^ dst) == 1u) return;
        const char* src = reinterpret_cast<const char*>(wq) + ofs;
#pragma unroll
        for (int i = 0; i < 8; i++)
            asm volatile("cp.async.cg.shared.global.L2::128B [%0], [%1], 16;" ::"r"(dst + i * 512), "l"(src + (size_t)((i >> 2) * 32 + (i & 3)) * 65536) : "memory");
        if ((warp & 3) == 3) {
            const uint32_t b = bars + 8 * (13 + (warp >> 2));
            if (lane == 0) mbar_init(b, 32);
            __syncwarp();
            asm volatile("cp.async.mbarrier.arrive.noinc.shared::cta.b64 [%0];" ::"r"(b) : "memory");
            bar_arrive(5, 96);
        }
    }
    cluster_arrive();
    uint32_t xn[8];
    uint32_t* const pqo = g_q + cta * 32 + lane;
    uint2* const pml = g_ml + cta * 4 + (g & 3);
    uint32_t* const po = g_o + ((h * 16 + (t & 1) * 8 + (warp >> 1)) * 16 + j) * 32 + (warp & 1) * 16 + (t >> 1) * 8 + g;
    unsigned long long* const pa = g_acc + (rank * 32 + (tid >> 3)) * 32 + (tid & 7);
    const int ocol = 256 * rank + 32 * warp + 8 * t + g;
    {
        const uint4 xa = __ldg(reinterpret_cast<const uint4*>(x) + lane);
        const uint4 xb = __ldg(reinterpret_cast<const uint4*>(x) + 32 + lane);
#pragma unroll
        for (int i = 0; i < 8; i++) xn[i] = __ldg(reinterpret_cast<const uint32_t*>(x) + (i >> 2) * 128 + warp * 16 + (i & 3) * 4 + t);
        if (pair == (tid >> 2)) atomicAdd(pa, to_fix(__bfloat162float(x[ocol])));
        const uint32_t xw[8] = {xa.x, xa.y, xa.z, xa.w, xb.x, xb.y, xb.z, xb.w};
        float s = 0.f;
#pragma unroll
        for (int i = 0; i < 8; i++) s += bflo(xw[i]) + bfhi(xw[i]);
#pragma unroll
        for (int o = 1; o < 32; o <<= 1) s += __shfl_xor_sync(~0u, s, o);
        const float mean = s * (1.f / D_MODEL);
        float q = 0.f;
#pragma unroll
        for (int i = 0; i < 8; i++) {
            const float a = bflo(xw[i]) - mean, b = bfhi(xw[i]) - mean;
            q += a * a + b * b;
        }
#pragma unroll
        for (int o = 1; o < 32; o <<= 1) q += __shfl_xor_sync(~0u, q, o);
        const float mb = bfr(mean);
        float sd;
        asm("sqrt.approx.f32 %0, %1;" : "=f"(sd) : "f"(bfr(bfr(q * (1.f / D_MODEL)) + 1e-5f)));
        const float rden = __fdividef(1.f, bfr(sd));
#pragma unroll
        for (int i = 0; i < 8; i++) xn[i] = pack_bf(bfr(bflo(xn[i]) - mb) * rden, bfr(bfhi(xn[i]) - mb) * rden);
    }
    asm volatile("cp.async.wait_all;" ::: "memory");
    __syncwarp();
    {
        float c0[4] = {0.f, 0.f, 0.f, 0.f}, c1[4] = {0.f, 0.f, 0.f, 0.f};
        const uint32_t base = sb + SM_W + (warp * 64 + lrow) * 64;
        const int sw = (lane >> 1) & 3;
#pragma unroll
        for (int s = 0; s < 4; s++) {
            uint32_t a[4], b[4];
            ldsm4t(a, base + s * 1024 + ((lch ^ sw) << 4));
            ldsm4t(b, base + s * 1024 + (((2 + lch) ^ sw) << 4));
            mma(c0, a[0], a[1], a[2], a[3], xn[2 * s], xn[2 * s + 1]);
            mma(c1, b[0], b[1], b[2], b[3], xn[2 * s], xn[2 * s + 1]);
        }
        reinterpret_cast<float*>(smem + SM_PART)[warp * 32 + 8 * t + g] = sel4(t, c0[0], c0[2], c1[0], c1[2]);
    }
    bar_arrive(2, 288);
    bar_sync(1, NTHREADS);
    const uint32_t tag = *reinterpret_cast<const uint32_t*>(smem + SM_TAG);
    if (warp == 0) {
        float s = 0.f;
#pragma unroll
        for (int w = 0; w < 8; w++) s += reinterpret_cast<const float*>(smem + SM_PART)[w * 32 + lane];
        st_pub1(pqo, __float_as_uint(bfr(s)) | tag);
    }
    if (tid < 128) {
        const uint4* pq = reinterpret_cast<const uint4*>(g_q + h * 512) + tid;
        uint4 v;
        delay(Q_DELAY);
#pragma unroll 1
        for (int it = 0; it < SPIN_LIMIT; it++) {
            v = ld_poll4(pq);
            if (tagged(v, tag)) break;
        }
        *reinterpret_cast<uint2*>(smem + SM_Q + warp * 272 + lane * 8) =
            make_uint2(__byte_perm(v.x, v.y, 0x7632), __byte_perm(v.z, v.w, 0x7632));
    }
    bar_sync(3, 256);
    const int head = g & 3;
    float sc[4];
    {
        uint32_t qa[4][4];
#pragma unroll
        for (int i = 0; i < 4; i++) ldsm4(qa[i], sb + SM_Q + (lane & 3) * 272 + (4 * i + (lane >> 3)) * 16);
        mbar_wait(bars + 8 * (warp >> 1));
        float c[4][4];
        const uint32_t kb = sb + SM_K + (warp >> 1) * 16384 + (32 * (warp & 1) + (lane & 7)) * 128;
#pragma unroll
        for (int n = 0; n < 4; n++) {
#pragma unroll
            for (int e = 0; e < 4; e++) c[n][e] = 0.f;
#pragma unroll
            for (int i = 0; i < 4; i++) {
                uint32_t b[4];
                ldsm4(b, kb + n * 1024 + (i >> 1) * 8192 + (((4 * (i & 1) + (lane >> 3)) ^ (lane & 7)) << 4));
                mma(c[n], qa[i][0], 0u, qa[i][1], 0u, b[0], b[1]);
                mma(c[n], qa[i][2], 0u, qa[i][3], 0u, b[2], b[3]);
            }
        }
        const bool up = g >= 4;
        const float scale = 0.08838834764831845f;
        sc[0] = bfr(bfr(up ? c[2][0] : c[0][0]) * scale);
        sc[1] = bfr(bfr(up ? c[2][1] : c[0][1]) * scale);
        sc[2] = bfr(bfr(up ? c[3][0] : c[1][0]) * scale);
        sc[3] = bfr(bfr(up ? c[3][1] : c[1][1]) * scale);
    }
    float mcta;
    {
        float m = fmaxf(fmaxf(sc[0], sc[1]), fmaxf(sc[2], sc[3]));
        m = fmaxf(m, __shfl_xor_sync(~0u, m, 1));
        m = fmaxf(m, __shfl_xor_sync(~0u, m, 2));
        m = fmaxf(m, __shfl_xor_sync(~0u, m, 16));
        if (t == 0 && g < 4) reinterpret_cast<float*>(smem + SM_MX)[g * 8 + warp] = m;
        bar_sync(3, 256);
        const float4 m0 = *reinterpret_cast<const float4*>(smem + SM_MX + head * 32);
        const float4 m1 = *reinterpret_cast<const float4*>(smem + SM_MX + head * 32 + 16);
        mcta = fmaxf(fmaxf(fmaxf(m0.x, m0.y), fmaxf(m0.z, m0.w)), fmaxf(fmaxf(m1.x, m1.y), fmaxf(m1.z, m1.w)));
        const float p0 = __expf(sc[0] - mcta), p1 = __expf(sc[1] - mcta), p2 = __expf(sc[2] - mcta), p3 = __expf(sc[3] - mcta);
        uint8_t* pp = smem + SM_P + head * 528 + (32 * warp + 16 * (g >> 2) + 2 * t) * 2;
        *reinterpret_cast<uint32_t*>(pp) = pack_bf(p0, p1);
        *reinterpret_cast<uint32_t*>(pp + 16) = pack_bf(p2, p3);
        float l = (p0 + p1) + (p2 + p3);
        l += __shfl_xor_sync(~0u, l, 1);
        l += __shfl_xor_sync(~0u, l, 2);
        l += __shfl_xor_sync(~0u, l, 16);
        if (t == 0 && g < 4) reinterpret_cast<float*>(smem + SM_SUM)[g * 8 + warp] = l;
        bar_sync(3, 256);
        if (warp == 0 && t == 0 && g < 4) {
            const float4 l0 = *reinterpret_cast<const float4*>(smem + SM_SUM + head * 32);
            const float4 l1 = *reinterpret_cast<const float4*>(smem + SM_SUM + head * 32 + 16);
            const float ls = ((l0.x + l0.y) + (l0.z + l0.w)) + ((l1.x + l1.y) + (l1.z + l1.w));
            st_pub2(pml, tagf(mcta, tag), tagf(ls, tag));
        }
    }
    {
        float c0[4] = {0.f, 0.f, 0.f, 0.f}, c1[4] = {0.f, 0.f, 0.f, 0.f};
        const uint32_t pb = sb + SM_P + (lane & 3) * 528 + (lane >> 3) * 16;
        const uint32_t vb = sb + SM_V + (warp >> 2) * 8192 + lrow * 128 + (((2 * (warp & 3) + lch) ^ (lane & 7)) << 4);
#pragma unroll
        for (int i = 0; i < 4; i++) {
            uint32_t p0[4], p1[4], a[4][4];
            ldsm4(p0, pb + i * 128);
            ldsm4(p1, pb + i * 128 + 64);
            mbar_wait(bars + 32 + 8 * i);
#pragma unroll
            for (int s = 0; s < 4; s++) ldsm4t(a[s], vb + i * 16384 + s * 2048);
            mma(c0, a[0][0], a[0][1], a[0][2], a[0][3], p0[0], p0[1]);
            mma(c1, a[1][0], a[1][1], a[1][2], a[1][3], p0[2], p0[3]);
            mma(c0, a[2][0], a[2][1], a[2][2], a[2][3], p1[0], p1[1]);
            mma(c1, a[3][0], a[3][1], a[3][2], a[3][3], p1[2], p1[3]);
        }
        const bool up = t >= 2;
        const float v0 = up ? c0[2] + c1[2] : c0[0] + c1[0];
        const float v1 = up ? c0[3] + c1[3] : c0[1] + c1[1];
        st_pub1(po, tagf(v0, tag));
        st_pub1(po + 4 * 512, tagf(v1, tag));
        if (warp == 0) bar_arrive(7, 64);
    }
    float y0[4] = {0.f, 0.f, 0.f, 0.f}, y1[4] = {0.f, 0.f, 0.f, 0.f};
    const uint32_t wofs = (warp >> 1) * 4096 + lrow * 128 + (((4 * (warp & 1) + lch) ^ (lane & 7)) << 4);
    if (has_ffn) {
        float c[4][4];
        const uint32_t base = sb + SM_G + (warp * 32 + lrow) * 64 + ((lch ^ ((lane >> 1) & 3)) << 4);
        const uint32_t x0 = rank ? xn[4] : xn[0], x1 = rank ? xn[5] : xn[1], x2 = rank ? xn[6] : xn[2], x3 = rank ? xn[7] : xn[3];
        cluster_wait();
#pragma unroll
        for (int m = 0; m < 4; m++) {
            uint32_t a[4], b[4];
            if (!(m & 1)) mbar_wait(bars + 64 + 4 * m);
            ldsm4t(a, (base ^ ((m & 1) << 5)) + (m >> 1) * 16384);
            ldsm4t(b, (base ^ ((m & 1) << 5)) + (m >> 1) * 16384 + 1024);
#pragma unroll
            for (int e = 0; e < 4; e++) c[m][e] = 0.f;
            mma(c[m], a[0], a[1], a[2], a[3], x0, x1);
            mma(c[m], b[0], b[1], b[2], b[3], x2, x3);
        }
        st_pair(sb + SM_PART2 + (rank * 8 + warp) * 256 + (8 * t + g) * 8, bars + 120,
                __float_as_uint(sel4(t, c[0][0], c[0][2], c[1][0], c[1][2])), __float_as_uint(sel4(t, c[2][0], c[2][2], c[3][0], c[3][2])));
        mbar_wait(bars + 120);
        float gs = 0.f, us = 0.f;
#pragma unroll
        for (int w = 0; w < 16; w++) {
            const float2 v = reinterpret_cast<const float2*>(smem + SM_PART2)[w * 32 + lane];
            gs += v.x;
            us += v.y;
        }
        gs = bfr(gs);
        const float hv = bfr(__fdividef(gs, 1.f + __expf(-gs))) * bfr(us);
        const uint32_t hp = pack_bf(hv, __shfl_down_sync(~0u, hv, 1));
        uint32_t hb[4];
#pragma unroll
        for (int i = 0; i < 4; i++) hb[i] = __shfl_sync(~0u, hp, 8 * i + 2 * t);
        mbar_wait(bars + 80);
#pragma unroll
        for (int s = 0; s < 2; s++) {
            uint32_t a[4], b[4];
            ldsm4t(a, sb + SM_D + s * 2048 + wofs);
            ldsm4t(b, sb + SM_D + s * 2048 + (wofs ^ 32));
            mma(y0, a[0], a[1], a[2], a[3], hb[2 * s], hb[2 * s + 1]);
            mma(y1, b[0], b[1], b[2], b[3], hb[2 * s], hb[2 * s + 1]);
        }
    }
    mbar_wait(bars + 128);
    {
        uint32_t ob[8];
#pragma unroll
        for (int i = 0; i < 8; i++) ob[i] = *reinterpret_cast<const uint32_t*>(smem + SM_O + i * 16 + t * 4);
        __nv_bfloat16* pout = out + ocol;
        asm volatile("" : "+l"(pout));
        float z0[4] = {0.f, 0.f, 0.f, 0.f}, z1[4] = {0.f, 0.f, 0.f, 0.f};
#pragma unroll
        for (int s = 0; s < 4; s++) {
            uint32_t a[4], b[4];
            if (!(s & 1)) mbar_wait(bars + 88 + 4 * s);
            ldsm4t(a, sb + SM_W + (s >> 1) * 16384 + (s & 1) * 2048 + wofs);
            ldsm4t(b, sb + SM_W + (s >> 1) * 16384 + (s & 1) * 2048 + (wofs ^ 32));
            mma((s & 1) ? z0 : y0, a[0], a[1], a[2], a[3], ob[2 * s], ob[2 * s + 1]);
            mma((s & 1) ? z1 : y1, b[0], b[1], b[2], b[3], ob[2 * s], ob[2 * s + 1]);
        }
        const unsigned long long f = to_fix(sel4(t, y0[0], y0[2], y1[0], y1[2]) + sel4(t, z0[0], z0[2], z1[0], z1[2]));
        const unsigned long long a = atomicAdd(pa, f) + (f - (NCTA / 2 + 1));
        if (((uint32_t)a & 255u) == 0) {
            asm volatile("st.global.u16 [%0], %1;" ::"l"(pout), "h"(__bfloat16_as_ushort(__float2bfloat16_rn(from_fix(a)))) : "memory");
            *pa = 0;
            if (ocol == 0) g_epoch = tag == TAGM ? 1u : tag + 1;
        }
    }
}

typedef CUresult (*EncodeFn)(CUtensorMap*, CUtensorMapDataType, cuuint32_t, void*, const cuuint64_t*, const cuuint64_t*,
                             const cuuint32_t*, const cuuint32_t*, CUtensorMapInterleave, CUtensorMapSwizzle,
                             CUtensorMapL2promotion, CUtensorMapFloatOOBfill);

void make_map(EncodeFn enc, CUtensorMap* m, void* p, uint64_t d0, uint64_t d1, uint64_t d2, uint64_t s1, uint64_t s2,
              uint32_t b0, uint32_t b1, uint32_t b2, CUtensorMapSwizzle sw) {
    cuuint64_t gd[3] = {d0, d1, d2};
    cuuint64_t gs[2] = {s1, s2};
    cuuint32_t bd[3] = {b0, b1, b2};
    cuuint32_t es[3] = {1, 1, 1};
    enc(m, CU_TENSOR_MAP_DATA_TYPE_BFLOAT16, 3, p, gd, gs, bd, es, CU_TENSOR_MAP_INTERLEAVE_NONE, sw,
        CU_TENSOR_MAP_L2_PROMOTION_L2_128B, CU_TENSOR_MAP_FLOAT_OOB_FILL_NONE);
}

}

extern "C" void kernel_launch(void* const* d_in, const int* in_sizes, int n_in, void* d_out, int out_size) {
    static EncodeFn enc = nullptr;
    if (!enc) {
        void* fn = nullptr;
        cudaDriverEntryPointQueryResult qr;
        cudaGetDriverEntryPoint("cuTensorMapEncodeTiled", &fn, cudaEnableDefault, &qr);
        enc = (EncodeFn)fn;
        cudaFuncSetAttribute(fused_decode_kernel, cudaFuncAttributeMaxDynamicSharedMemorySize, SM_TOTAL);
    }
    Maps m;
    make_map(enc, &m.m[0], d_in[1], 64, (uint64_t)HKV * SK, 2, DH * 2, 128, 64, 64, 2, CU_TENSOR_MAP_SWIZZLE_128B);
    make_map(enc, &m.m[1], d_in[2], 64, (uint64_t)HKV * SK, 2, DH * 2, 128, 64, 64, 2, CU_TENSOR_MAP_SWIZZLE_128B);
    make_map(enc, &m.m[2], d_in[6], FF, 256, 2, FF * 2, FF * 2 * 256, 32, 256, 1, CU_TENSOR_MAP_SWIZZLE_64B);
    make_map(enc, &m.m[3], d_in[7], FF, 256, 2, FF * 2, FF * 2 * 256, 32, 256, 1, CU_TENSOR_MAP_SWIZZLE_64B);
    make_map(enc, &m.m[4], d_in[8], 64, FF, 8, D_MODEL * 2, 128, 64, 32, 4, CU_TENSOR_MAP_SWIZZLE_128B);
    make_map(enc, &m.m[5], d_in[4], 64, 4096, 8, D_MODEL * 2, 128, 64, 32, 4, CU_TENSOR_MAP_SWIZZLE_128B);
    fused_decode_kernel<<<NCTA, NTHREADS, SM_TOTAL>>>((const __nv_bfloat16*)d_in[0], (const __nv_bfloat16*)d_in[3],
                                                      (__nv_bfloat16*)d_out, m);
}
```
